```python
import torch

def _softmax(x, axis=-1):
    return torch.softmax(x, dim=axis)
def _gelu(x):
    return torch.nn.functional.gelu(x, approximate="tanh")
def _silu(x):
    return torch.nn.functional.silu(x)
def _sigmoid(x):
    return torch.sigmoid(x)
def _layernorm(x, axis=-1, eps=1e-5):
    m = x.mean(dim=axis, keepdim=True)
    v = x.var(dim=axis, keepdim=True, unbiased=False)
    return (x - m) / torch.sqrt(v + eps)
def _scatter_add(tgt, idx, src, axis=0):
    return tgt.clone().index_add_(axis, idx, src)
def _segment_sum(src, seg, n):
    out = torch.zeros((n,) + src.shape[1:], dtype=src.dtype)
    return out.index_add_(0, seg, src)
def _pad(x, pw):
    flat = tuple(v for pair in reversed(pw) for v in pair)
    return torch.nn.functional.pad(x, flat)

kernel_name = 'concat_heads__linear_kernel_hedgehog__ssm_conv_s5__prompt'

def setup_inputs():

    _w = (lambda a: (lambda t: t.to(torch.bfloat16) if t.is_floating_point() else t)(torch.as_tensor(a)))
    def _A_setup():
        B, S, D, H = 1, 2048, 640, 32
        Dh = D // H
        return {
            "x": _w((lambda *s: torch.randn(*s, dtype=torch.bfloat16) * 0.4)(B, S, D)),
            "wqkv": _w((lambda *s: torch.randn(*s, dtype=torch.bfloat16) * 0.4)(D, 3 * D)),
            "w_phi": _w((lambda *s: torch.randn(*s, dtype=torch.bfloat16) * 0.4)(H, Dh, Dh) * (Dh ** -0.5)),
            "wo": _w((lambda *s: torch.randn(*s, dtype=torch.bfloat16) * 0.05)(D, D)),
        }
    _A_in = _A_setup()

    def _B_setup():
        B, S, D = 1, 2048, 640
        P = D
        Lambda_re = -0.5 * (lambda _x: torch.exp(torch.as_tensor(_x)))((lambda *s: torch.randn(*s, dtype=torch.bfloat16) * 0.8)(P))
        Lambda_im = (lambda *s: torch.randn(*s, dtype=torch.bfloat16) * 0.8)(P) * 1.0
        B_re = (lambda *s: torch.randn(*s, dtype=torch.bfloat16) * 0.8)(P, D) * (D ** -0.5)
        B_im = (lambda *s: torch.randn(*s, dtype=torch.bfloat16) * 0.8)(P, D) * (D ** -0.5)
        C_re = (lambda *s: torch.randn(*s, dtype=torch.bfloat16) * 0.8)(D, P) * (P ** -0.5)
        C_im = (lambda *s: torch.randn(*s, dtype=torch.bfloat16) * 0.8)(D, P) * (P ** -0.5)
        log_dt = (lambda *s: torch.randn(*s, dtype=torch.bfloat16) * 0.8)(P) * 0.3 - 2.0
        Dskip = (lambda *s: torch.randn(*s, dtype=torch.bfloat16) * 0.8)(D)
        return {
            "x": _w((lambda *s: torch.randn(*s, dtype=torch.bfloat16) * 0.05)(B, S, D)),
            "Lambda_re": _w(Lambda_re),
            "Lambda_im": _w(Lambda_im),
            "B_re": _w(B_re),
            "B_im": _w(B_im),
            "C_re": _w(C_re),
            "C_im": _w(C_im),
            "log_dt": _w(log_dt),
            "Dskip": _w(Dskip),
        }
    _B_in = _B_setup()

    return {
        "A_x": _A_in["x"],
        "A_wqkv": _A_in["wqkv"],
        "A_w_phi": _A_in["w_phi"],
        "A_wo": _A_in["wo"],
        "B_x": _B_in["x"],
        "B_Lambda_re": _B_in["Lambda_re"],
        "B_Lambda_im": _B_in["Lambda_im"],
        "B_B_re": _B_in["B_re"],
        "B_B_im": _B_in["B_im"],
        "B_C_re": _B_in["C_re"],
        "B_C_im": _B_in["C_im"],
        "B_log_dt": _B_in["log_dt"],
        "B_Dskip": _B_in["Dskip"],
    }

def reference(A_x, A_wqkv, A_w_phi, A_wo, B_x, B_Lambda_re, B_Lambda_im, B_B_re, B_B_im, B_C_re, B_C_im, B_log_dt, B_Dskip):
    def _A_ref(x, wqkv, w_phi, wo):
        B, S, D = x.shape
        H = 32; Dh = D // H
        qkv = (lambda x, *d: x.permute(*d))((x @ wqkv).reshape(B, S, 3, H, Dh), 2, 0, 3, 1, 4)
        q, k, v = qkv[0], qkv[1], qkv[2]
        pq = torch.einsum("bhsd,hdf->bhsf", q, w_phi)
        pk = torch.einsum("bhsd,hdf->bhsf", k, w_phi)
        phi_q = torch.concatenate([_softmax(pq, axis=-1), _softmax(-pq, axis=-1)], axis=-1)
        phi_k = torch.concatenate([_softmax(pk, axis=-1), _softmax(-pk, axis=-1)], axis=-1)
        kv = torch.einsum("bhsf,bhsd->bhfd", phi_k, v)
        z  = torch.einsum("bhsf->bhf", phi_k)
        num = torch.einsum("bhqf,bhfd->bhqd", phi_q, kv)
        den = torch.einsum("bhqf,bhf->bhq", phi_q, z)[..., None] + 1e-6
        o = num / den
        return (lambda x, *d: x.permute(*d))(o, 0, 2, 1, 3).reshape(B, S, D) @ wo

    def _B_ref(x, Lambda_re, Lambda_im, B_re, B_im, C_re, C_im, log_dt, Dskip):
        Bsz, L, H = x.shape
        Lam = Lambda_re + 1j * Lambda_im
        Bmat = B_re + 1j * B_im
        Cmat = C_re + 1j * C_im
        dt = torch.exp(log_dt)
        Lam_bar = torch.exp(dt * Lam)
        B_bar = ((Lam_bar - 1.0) / Lam)[:, None] * Bmat
        Bu = torch.einsum("bld,pd->blp", x + 0j, B_bar)
        h = torch.zeros_like(Bu[:, 0, :])
        hs = []
        for t in range(L):
            h = Lam_bar[None, :] * h + Bu[:, t, :]
            hs.append(h)
        hseq = torch.stack(hs, 1)
        y = 2.0 * torch.einsum("blp,dp->bld", hseq, Cmat).real + x * Dskip[None, None, :]
        return y

    a = _A_ref(A_x, A_wqkv, A_w_phi, A_wo)
    b = _B_ref(B_x, B_Lambda_re, B_Lambda_im, B_B_re, B_B_im, B_C_re, B_C_im, B_log_dt, B_Dskip)
    return torch.concatenate([a, b], axis=-1)
```

```cpp
#define B_PS 4
#include <cuda_runtime.h>
#include <cuda_bf16.h>
#include <cuda.h>
#include <stdint.h>

namespace {

constexpr int kSeq = 2048;
constexpr int kD = 640;
constexpr int kGrid = 132;
constexpr int kThreads = 384;

constexpr uint32_t kBlob = 20480;
constexpr uint32_t kFold = 19456;
constexpr uint32_t kPair = 5152;
constexpr uint32_t kHalf = 20576;
constexpr uint32_t kKvBytes = 26880;
constexpr int A_NS = 5;

constexpr uint32_t SB = 1024;
constexpr uint32_t BARS = SB;
constexpr uint32_t A_Z = SB + 576;
constexpr uint32_t A_PHI = A_Z + 6400;
constexpr uint32_t A_X = A_PHI + 2 * kHalf;
constexpr uint32_t A_RING = A_X + 81920;
constexpr uint32_t B_RING = SB + 1024;
constexpr uint32_t B_SLOT = 36864;
constexpr uint32_t B_STG = B_RING + 5 * B_SLOT;
constexpr uint32_t B_ZERO = B_STG + 40960;
constexpr uint32_t B_CONST = B_ZERO + 2688;
constexpr uint32_t kSmem = 232448;

constexpr uint32_t BAR_FULL = BARS, BAR_EMPTY = BARS + 48, BAR_TOK = BARS + 96, BAR_STG = BARS + 112, BAR_V = BARS + 120,
                   BAR_O = BARS + 128, BAR_KV0 = BARS + 144, BAR_P = BARS + 152, BAR_KVR = BARS + 160, BAR_P1 = BARS + 176,
                   BAR_X = BARS + 184, BAR_FREE = BARS + 264, BAR_RED = BARS + 280, BAR_DONE = BARS + 296, BAR_W = BARS + 304,
                   BAR_DUMMY = BARS + 328, BAR_PREP = BARS + 336, BAR_QD = BARS + 344, BAR_QF = BARS + 352,
                   BAR_STG1 = BARS + 360;
__host__ __device__ constexpr uint32_t bar_count(uint32_t a) {
  return a == BAR_DONE ? 11 : a == BAR_PREP ? 8 : a == BAR_DUMMY ? 1024
       : (a == BAR_TOK || a == BAR_TOK + 8 || a == BAR_V || a == BAR_O || a == BAR_O + 8 || (a >= BAR_FREE && a < BAR_DONE) || a == BAR_QD || a == BAR_QF) ? 4 : 1;
}
constexpr uint32_t kPrepW = 24576, kPrepPhi = 6400;
enum { C_W = 0, C_KV = 12, C_H = 16, C_O = 42, C_COUNT = 42 + 128 };

struct Scratch {
  unsigned char w[3 * 4 * 10 * kBlob];
  unsigned char ox[32 * 4 * kBlob];
  unsigned char h[13 * 20 * kBlob];
  float kv[4 * 6720];
  unsigned long long fin[13 * 640];
  unsigned cnt[C_COUNT * 32];
  unsigned ep[kGrid * 32];
};
__device__ __align__(1024) Scratch g_scratch;

struct Params {
  Scratch* s;
  float* out;
  const __nv_bfloat16 *wphi, *cre_p, *cim_p, *lre, *lim, *logdt, *dskip;
  int one;
  CUtensorMap xa, wv, wp, xb, bre, bim, xbl, cre, cim, wop;
};

#define TS(slot)
#define TS1(slot)
#define ST(i)

template <int TB>
__device__ __forceinline__ void wgmma_n128(float* d, uint64_t da, uint64_t db, int sc) {
  asm volatile("{ .reg .pred p; setp.ne.b32 p, %66, 0;\n"
    "wgmma.mma_async.sync.aligned.m64n128k16.f32.bf16.bf16 {%0,%1,%2,%3,%4,%5,%6,%7,%8,%9,%10,%11,%12,%13,%14,%15,%16,%17,%18,%19,%20,%21,%22,%23,%24,%25,%26,%27,%28,%29,%30,%31,%32,%33,%34,%35,%36,%37,%38,%39,%40,%41,%42,%43,%44,%45,%46,%47,%48,%49,%50,%51,%52,%53,%54,%55,%56,%57,%58,%59,%60,%61,%62,%63}, %64, %65, p, 1, 1, 0, %67; }"
    : "+f"(d[0]),"+f"(d[1]),"+f"(d[2]),"+f"(d[3]),"+f"(d[4]),"+f"(d[5]),"+f"(d[6]),"+f"(d[7]),"+f"(d[8]),"+f"(d[9]),"+f"(d[10]),"+f"(d[11]),"+f"(d[12]),"+f"(d[13]),"+f"(d[14]),"+f"(d[15]),"+f"(d[16]),"+f"(d[17]),"+f"(d[18]),"+f"(d[19]),"+f"(d[20]),"+f"(d[21]),"+f"(d[22]),"+f"(d[23]),"+f"(d[24]),"+f"(d[25]),"+f"(d[26]),"+f"(d[27]),"+f"(d[28]),"+f"(d[29]),"+f"(d[30]),"+f"(d[31]),"+f"(d[32]),"+f"(d[33]),"+f"(d[34]),"+f"(d[35]),"+f"(d[36]),"+f"(d[37]),"+f"(d[38]),"+f"(d[39]),"+f"(d[40]),"+f"(d[41]),"+f"(d[42]),"+f"(d[43]),"+f"(d[44]),"+f"(d[45]),"+f"(d[46]),"+f"(d[47]),"+f"(d[48]),"+f"(d[49]),"+f"(d[50]),"+f"(d[51]),"+f"(d[52]),"+f"(d[53]),"+f"(d[54]),"+f"(d[55]),"+f"(d[56]),"+f"(d[57]),"+f"(d[58]),"+f"(d[59]),"+f"(d[60]),"+f"(d[61]),"+f"(d[62]),"+f"(d[63])
    : "l"(da), "l"(db), "r"(sc), "n"(TB));
}
template <int TB>
__device__ __forceinline__ void wgmma_n192(float* d, uint64_t da, uint64_t db, int sc) {
  asm volatile("{ .reg .pred p; setp.ne.b32 p, %98, 0;\n"
    "wgmma.mma_async.sync.aligned.m64n192k16.f32.bf16.bf16 {%0,%1,%2,%3,%4,%5,%6,%7,%8,%9,%10,%11,%12,%13,%14,%15,%16,%17,%18,%19,%20,%21,%22,%23,%24,%25,%26,%27,%28,%29,%30,%31,%32,%33,%34,%35,%36,%37,%38,%39,%40,%41,%42,%43,%44,%45,%46,%47,%48,%49,%50,%51,%52,%53,%54,%55,%56,%57,%58,%59,%60,%61,%62,%63,%64,%65,%66,%67,%68,%69,%70,%71,%72,%73,%74,%75,%76,%77,%78,%79,%80,%81,%82,%83,%84,%85,%86,%87,%88,%89,%90,%91,%92,%93,%94,%95}, %96, %97, p, 1, 1, 0, %99; }"
    : "+f"(d[0]),"+f"(d[1]),"+f"(d[2]),"+f"(d[3]),"+f"(d[4]),"+f"(d[5]),"+f"(d[6]),"+f"(d[7]),"+f"(d[8]),"+f"(d[9]),"+f"(d[10]),"+f"(d[11]),"+f"(d[12]),"+f"(d[13]),"+f"(d[14]),"+f"(d[15]),"+f"(d[16]),"+f"(d[17]),"+f"(d[18]),"+f"(d[19]),"+f"(d[20]),"+f"(d[21]),"+f"(d[22]),"+f"(d[23]),"+f"(d[24]),"+f"(d[25]),"+f"(d[26]),"+f"(d[27]),"+f"(d[28]),"+f"(d[29]),"+f"(d[30]),"+f"(d[31]),"+f"(d[32]),"+f"(d[33]),"+f"(d[34]),"+f"(d[35]),"+f"(d[36]),"+f"(d[37]),"+f"(d[38]),"+f"(d[39]),"+f"(d[40]),"+f"(d[41]),"+f"(d[42]),"+f"(d[43]),"+f"(d[44]),"+f"(d[45]),"+f"(d[46]),"+f"(d[47]),"+f"(d[48]),"+f"(d[49]),"+f"(d[50]),"+f"(d[51]),"+f"(d[52]),"+f"(d[53]),"+f"(d[54]),"+f"(d[55]),"+f"(d[56]),"+f"(d[57]),"+f"(d[58]),"+f"(d[59]),"+f"(d[60]),"+f"(d[61]),"+f"(d[62]),"+f"(d[63]),"+f"(d[64]),"+f"(d[65]),"+f"(d[66]),"+f"(d[67]),"+f"(d[68]),"+f"(d[69]),"+f"(d[70]),"+f"(d[71]),"+f"(d[72]),"+f"(d[73]),"+f"(d[74]),"+f"(d[75]),"+f"(d[76]),"+f"(d[77]),"+f"(d[78]),"+f"(d[79]),"+f"(d[80]),"+f"(d[81]),"+f"(d[82]),"+f"(d[83]),"+f"(d[84]),"+f"(d[85]),"+f"(d[86]),"+f"(d[87]),"+f"(d[88]),"+f"(d[89]),"+f"(d[90]),"+f"(d[91]),"+f"(d[92]),"+f"(d[93]),"+f"(d[94]),"+f"(d[95])
    : "l"(da), "l"(db), "r"(sc), "n"(TB));
}

__device__ __forceinline__ void wg_fence() { asm volatile("wgmma.fence.sync.aligned;" ::: "memory"); }
__device__ __forceinline__ void wg_commit() { asm volatile("wgmma.commit_group.sync.aligned;" ::: "memory"); }
template <int N> __device__ __forceinline__ void wg_wait() { asm volatile("wgmma.wait_group.sync.aligned %0;" ::"n"(N) : "memory"); }
template <int N> __device__ __forceinline__ void reg_fence(float* d) {
#pragma unroll
  for (int i = 0; i < N; i++) asm volatile("" : "+f"(d[i])::"memory");
}
template <int N> __device__ __forceinline__ void reg_kill(float* d) {
#pragma unroll
  for (int i = 0; i < N; i++) asm volatile("" : "=f"(d[i]));
}
__host__ __device__ constexpr uint32_t desc_lo(uint32_t addr, uint32_t lbo) { return (addr >> 4) | ((lbo >> 4) << 16); }
constexpr uint32_t kHiSw128 = (1024 >> 4) | (1u << 30);
constexpr uint32_t kHiPlain = 128 >> 4;
__device__ __forceinline__ uint64_t mkdesc(uint32_t lo, uint32_t hi) { return ((uint64_t)hi << 32) | lo; }
__device__ __forceinline__ int uniform(int v) { return __shfl_sync(~0u, v, 0); }

__device__ __forceinline__ void a_mainloop152(float* d, uint32_t& s8, uint32_t da, uint32_t ph, int n, int sc, uint32_t xw) {
  asm volatile(
    "{ .reg .pred pe, pw, pl, ps, pt; .reg .b32 da, db, ha, hb, s8, ph, n, xw, pa, t, u; .reg .b64 dA, dB;\n"
    "mov.b32 s8, %76; mov.b32 da, %77; mov.b32 ph, %78; mov.b32 n, %79; mov.b32 xw, %81; mov.b32 pa, %85; mov.b32 hb, %86; mov.b32 ha, %87;\n"
    "mov.u32 t, %%laneid; setp.lt.u32 pe, t, 2; setp.ne.b32 ps, %80, 0; setp.eq.b32 pt, 0, 0;\n"
    "add.u32 u, s8, %83; mad.lo.u32 db, s8, 160, %82;\n"
    "LOOP:\n"
    "W0: mbarrier.try_wait.parity.shared::cta.b64 pw, [u], ph, 100000;\n"
    "@!pw bra W0;\n"
    "wgmma.fence.sync.aligned;\n"
    "mov.b64 dA, {da, ha}; mov.b64 dB, {db, hb};\n"
    "wgmma.mma_async.sync.aligned.m64n152k16.f32.bf16.bf16 {%0,%1,%2,%3,%4,%5,%6,%7,%8,%9,%10,%11,%12,%13,%14,%15,%16,%17,%18,%19,%20,%21,%22,%23,%24,%25,%26,%27,%28,%29,%30,%31,%32,%33,%34,%35,%36,%37,%38,%39,%40,%41,%42,%43,%44,%45,%46,%47,%48,%49,%50,%51,%52,%53,%54,%55,%56,%57,%58,%59,%60,%61,%62,%63,%64,%65,%66,%67,%68,%69,%70,%71,%72,%73,%74,%75}, dA, dB, ps, 1, 1, 0, 0;\n"
    "add.u32 t, da, 2; add.u32 u, db, 2;\n"
    "mov.b64 dA, {t, ha}; mov.b64 dB, {u, hb};\n"
    "wgmma.mma_async.sync.aligned.m64n152k16.f32.bf16.bf16 {%0,%1,%2,%3,%4,%5,%6,%7,%8,%9,%10,%11,%12,%13,%14,%15,%16,%17,%18,%19,%20,%21,%22,%23,%24,%25,%26,%27,%28,%29,%30,%31,%32,%33,%34,%35,%36,%37,%38,%39,%40,%41,%42,%43,%44,%45,%46,%47,%48,%49,%50,%51,%52,%53,%54,%55,%56,%57,%58,%59,%60,%61,%62,%63,%64,%65,%66,%67,%68,%69,%70,%71,%72,%73,%74,%75}, dA, dB, pt, 1, 1, 0, 0;\n"
    "wgmma.commit_group.sync.aligned;\n"
    "wgmma.wait_group.sync.aligned 1;\n"
    "@pe mbarrier.arrive.shared::cta.b64 _, [pa];\n"
    "add.u32 pa, s8, %84;\n"
    "add.u32 t, da, 4; add.u32 u, db, 4;\n"
    "mov.b64 dA, {t, ha}; mov.b64 dB, {u, hb};\n"
    "wgmma.mma_async.sync.aligned.m64n152k16.f32.bf16.bf16 {%0,%1,%2,%3,%4,%5,%6,%7,%8,%9,%10,%11,%12,%13,%14,%15,%16,%17,%18,%19,%20,%21,%22,%23,%24,%25,%26,%27,%28,%29,%30,%31,%32,%33,%34,%35,%36,%37,%38,%39,%40,%41,%42,%43,%44,%45,%46,%47,%48,%49,%50,%51,%52,%53,%54,%55,%56,%57,%58,%59,%60,%61,%62,%63,%64,%65,%66,%67,%68,%69,%70,%71,%72,%73,%74,%75}, dA, dB, pt, 1, 1, 0, 0;\n"
    "add.u32 s8, s8, 8; setp.eq.b32 pw, s8, %88; @pw mov.b32 s8, 0; @pw xor.b32 ph, ph, 1; sub.u32 n, n, 1; setp.ne.b32 pl, n, 0; setp.eq.b32 ps, 0, 0;\n"
    "add.u32 t, da, 6; add.u32 u, db, 6;\n"
    "mov.b64 dA, {t, ha}; mov.b64 dB, {u, hb};\n"
    "wgmma.mma_async.sync.aligned.m64n152k16.f32.bf16.bf16 {%0,%1,%2,%3,%4,%5,%6,%7,%8,%9,%10,%11,%12,%13,%14,%15,%16,%17,%18,%19,%20,%21,%22,%23,%24,%25,%26,%27,%28,%29,%30,%31,%32,%33,%34,%35,%36,%37,%38,%39,%40,%41,%42,%43,%44,%45,%46,%47,%48,%49,%50,%51,%52,%53,%54,%55,%56,%57,%58,%59,%60,%61,%62,%63,%64,%65,%66,%67,%68,%69,%70,%71,%72,%73,%74,%75}, dA, dB, pt, 1, 1, 0, 0;\n"
    "wgmma.commit_group.sync.aligned;\n"
    "add.u32 da, da, 512; add.u32 u, s8, %83; mad.lo.u32 db, s8, 160, %82;\n"
    "@pl bra LOOP;\n"
    "mov.b32 %76, pa; }\n"
    : "+f"(d[0]),"+f"(d[1]),"+f"(d[2]),"+f"(d[3]),"+f"(d[4]),"+f"(d[5]),"+f"(d[6]),"+f"(d[7]),"+f"(d[8]),"+f"(d[9]),"+f"(d[10]),"+f"(d[11]),"+f"(d[12]),"+f"(d[13]),"+f"(d[14]),"+f"(d[15]),"+f"(d[16]),"+f"(d[17]),"+f"(d[18]),"+f"(d[19]),"+f"(d[20]),"+f"(d[21]),"+f"(d[22]),"+f"(d[23]),"+f"(d[24]),"+f"(d[25]),"+f"(d[26]),"+f"(d[27]),"+f"(d[28]),"+f"(d[29]),"+f"(d[30]),"+f"(d[31]),"+f"(d[32]),"+f"(d[33]),"+f"(d[34]),"+f"(d[35]),"+f"(d[36]),"+f"(d[37]),"+f"(d[38]),"+f"(d[39]),"+f"(d[40]),"+f"(d[41]),"+f"(d[42]),"+f"(d[43]),"+f"(d[44]),"+f"(d[45]),"+f"(d[46]),"+f"(d[47]),"+f"(d[48]),"+f"(d[49]),"+f"(d[50]),"+f"(d[51]),"+f"(d[52]),"+f"(d[53]),"+f"(d[54]),"+f"(d[55]),"+f"(d[56]),"+f"(d[57]),"+f"(d[58]),"+f"(d[59]),"+f"(d[60]),"+f"(d[61]),"+f"(d[62]),"+f"(d[63]),"+f"(d[64]),"+f"(d[65]),"+f"(d[66]),"+f"(d[67]),"+f"(d[68]),"+f"(d[69]),"+f"(d[70]),"+f"(d[71]),"+f"(d[72]),"+f"(d[73]),"+f"(d[74]),"+f"(d[75]), "+r"(s8)
    : "r"(da), "r"(ph), "r"(n), "r"(sc), "r"(xw), "n"(desc_lo(A_RING, 16)), "n"(BAR_FULL), "n"(BAR_EMPTY),
      "n"(BAR_DUMMY), "n"(kHiSw128), "n"(kHiSw128), "n"(8 * A_NS)
    : "memory");
}
__device__ __forceinline__ void a_mainloop160(float* d, uint32_t& s8, uint32_t da, uint32_t ph, int n, int sc, uint32_t xw) {
  asm volatile(
    "{ .reg .pred pe, pw, pl, ps, pt; .reg .b32 da, db, ha, hb, s8, ph, n, xw, pa, t, u; .reg .b64 dA, dB;\n"
    "mov.b32 s8, %80; mov.b32 da, %81; mov.b32 ph, %82; mov.b32 n, %83; mov.b32 xw, %85; mov.b32 pa, %89; mov.b32 hb, %90; mov.b32 ha, %91;\n"
    "mov.u32 t, %%laneid; setp.lt.u32 pe, t, 2; setp.ne.b32 ps, %84, 0; setp.eq.b32 pt, 0, 0;\n"
    "add.u32 u, s8, %87; mad.lo.u32 db, s8, 160, %86;\n"
    "LOOP:\n"
    "W0: mbarrier.try_wait.parity.shared::cta.b64 pw, [u], ph, 100000;\n"
    "@!pw bra W0;\n"
    "wgmma.fence.sync.aligned;\n"
    "mov.b64 dA, {da, ha}; mov.b64 dB, {db, hb};\n"
    "wgmma.mma_async.sync.aligned.m64n160k16.f32.bf16.bf16 {%0,%1,%2,%3,%4,%5,%6,%7,%8,%9,%10,%11,%12,%13,%14,%15,%16,%17,%18,%19,%20,%21,%22,%23,%24,%25,%26,%27,%28,%29,%30,%31,%32,%33,%34,%35,%36,%37,%38,%39,%40,%41,%42,%43,%44,%45,%46,%47,%48,%49,%50,%51,%52,%53,%54,%55,%56,%57,%58,%59,%60,%61,%62,%63,%64,%65,%66,%67,%68,%69,%70,%71,%72,%73,%74,%75,%76,%77,%78,%79}, dA, dB, ps, 1, 1, 0, 0;\n"
    "add.u32 t, da, 128; add.u32 u, db, 2;\n"
    "mov.b64 dA, {t, ha}; mov.b64 dB, {u, hb};\n"
    "wgmma.mma_async.sync.aligned.m64n160k16.f32.bf16.bf16 {%0,%1,%2,%3,%4,%5,%6,%7,%8,%9,%10,%11,%12,%13,%14,%15,%16,%17,%18,%19,%20,%21,%22,%23,%24,%25,%26,%27,%28,%29,%30,%31,%32,%33,%34,%35,%36,%37,%38,%39,%40,%41,%42,%43,%44,%45,%46,%47,%48,%49,%50,%51,%52,%53,%54,%55,%56,%57,%58,%59,%60,%61,%62,%63,%64,%65,%66,%67,%68,%69,%70,%71,%72,%73,%74,%75,%76,%77,%78,%79}, dA, dB, pt, 1, 1, 0, 0;\n"
    "wgmma.commit_group.sync.aligned;\n"
    "wgmma.wait_group.sync.aligned 1;\n"
    "@pe mbarrier.arrive.shared::cta.b64 _, [pa];\n"
    "add.u32 pa, s8, %88;\n"
    "W2: mbarrier.try_wait.parity.shared::cta.b64 pw, [xw], 0, 100000;\n"
    "@!pw bra W2;\n"
    "wgmma.fence.sync.aligned;\n"
    "add.u32 xw, xw, 8;\n"
    "add.u32 t, da, 256; add.u32 u, db, 4;\n"
    "mov.b64 dA, {t, ha}; mov.b64 dB, {u, hb};\n"
    "wgmma.mma_async.sync.aligned.m64n160k16.f32.bf16.bf16 {%0,%1,%2,%3,%4,%5,%6,%7,%8,%9,%10,%11,%12,%13,%14,%15,%16,%17,%18,%19,%20,%21,%22,%23,%24,%25,%26,%27,%28,%29,%30,%31,%32,%33,%34,%35,%36,%37,%38,%39,%40,%41,%42,%43,%44,%45,%46,%47,%48,%49,%50,%51,%52,%53,%54,%55,%56,%57,%58,%59,%60,%61,%62,%63,%64,%65,%66,%67,%68,%69,%70,%71,%72,%73,%74,%75,%76,%77,%78,%79}, dA, dB, pt, 1, 1, 0, 0;\n"
    "add.u32 s8, s8, 8; setp.eq.b32 pw, s8, %92; @pw mov.b32 s8, 0; @pw xor.b32 ph, ph, 1; sub.u32 n, n, 1; setp.ne.b32 pl, n, 0; setp.eq.b32 ps, 0, 0;\n"
    "add.u32 t, da, 384; add.u32 u, db, 6;\n"
    "mov.b64 dA, {t, ha}; mov.b64 dB, {u, hb};\n"
    "wgmma.mma_async.sync.aligned.m64n160k16.f32.bf16.bf16 {%0,%1,%2,%3,%4,%5,%6,%7,%8,%9,%10,%11,%12,%13,%14,%15,%16,%17,%18,%19,%20,%21,%22,%23,%24,%25,%26,%27,%28,%29,%30,%31,%32,%33,%34,%35,%36,%37,%38,%39,%40,%41,%42,%43,%44,%45,%46,%47,%48,%49,%50,%51,%52,%53,%54,%55,%56,%57,%58,%59,%60,%61,%62,%63,%64,%65,%66,%67,%68,%69,%70,%71,%72,%73,%74,%75,%76,%77,%78,%79}, dA, dB, pt, 1, 1, 0, 0;\n"
    "wgmma.commit_group.sync.aligned;\n"
    "add.u32 da, da, 512; add.u32 u, s8, %87; mad.lo.u32 db, s8, 160, %86;\n"
    "@pl bra LOOP;\n"
    "mov.b32 %80, pa; }\n"
    : "+f"(d[0]),"+f"(d[1]),"+f"(d[2]),"+f"(d[3]),"+f"(d[4]),"+f"(d[5]),"+f"(d[6]),"+f"(d[7]),"+f"(d[8]),"+f"(d[9]),"+f"(d[10]),"+f"(d[11]),"+f"(d[12]),"+f"(d[13]),"+f"(d[14]),"+f"(d[15]),"+f"(d[16]),"+f"(d[17]),"+f"(d[18]),"+f"(d[19]),"+f"(d[20]),"+f"(d[21]),"+f"(d[22]),"+f"(d[23]),"+f"(d[24]),"+f"(d[25]),"+f"(d[26]),"+f"(d[27]),"+f"(d[28]),"+f"(d[29]),"+f"(d[30]),"+f"(d[31]),"+f"(d[32]),"+f"(d[33]),"+f"(d[34]),"+f"(d[35]),"+f"(d[36]),"+f"(d[37]),"+f"(d[38]),"+f"(d[39]),"+f"(d[40]),"+f"(d[41]),"+f"(d[42]),"+f"(d[43]),"+f"(d[44]),"+f"(d[45]),"+f"(d[46]),"+f"(d[47]),"+f"(d[48]),"+f"(d[49]),"+f"(d[50]),"+f"(d[51]),"+f"(d[52]),"+f"(d[53]),"+f"(d[54]),"+f"(d[55]),"+f"(d[56]),"+f"(d[57]),"+f"(d[58]),"+f"(d[59]),"+f"(d[60]),"+f"(d[61]),"+f"(d[62]),"+f"(d[63]),"+f"(d[64]),"+f"(d[65]),"+f"(d[66]),"+f"(d[67]),"+f"(d[68]),"+f"(d[69]),"+f"(d[70]),"+f"(d[71]),"+f"(d[72]),"+f"(d[73]),"+f"(d[74]),"+f"(d[75]),"+f"(d[76]),"+f"(d[77]),"+f"(d[78]),"+f"(d[79]), "+r"(s8)
    : "r"(da), "r"(ph), "r"(n), "r"(sc), "r"(xw), "n"(desc_lo(A_RING, 16)), "n"(BAR_FULL), "n"(BAR_EMPTY),
      "n"(BAR_DUMMY), "n"(kHiSw128), "n"(kHiPlain), "n"(8 * A_NS)
    : "memory");
}
__device__ __forceinline__ void b_mainloop(float* d, float* e, int sc, int own, int pause, uint32_t pa, uint32_t pb) {
  asm volatile(
    "{ .reg .pred pe, pw, pl, ps, pt; .reg .b32 da, db, dv, hb, s8, ph, n, pa, t, u; .reg .b64 dA, dB;\n"
    "mov.b32 s8, 0; mov.b32 ph, 0; mov.b32 n, 10; mov.b32 pa, %164; mov.b32 hb, %165; mov.b32 dv, %166;\n"
    "mov.u32 t, %%laneid; setp.eq.u32 pe, t, 0; setp.ne.b32 ps, %160, 0; setp.eq.b32 pt, 0, 0;\n"
    "LOOP: add.u32 u, s8, %162;\n"
    "W0: mbarrier.try_wait.parity.shared::cta.b64 pw, [u], ph, 100000;\n"
    "@!pw bra W0;\n"
    "mad.lo.u32 da, s8, 288, %161; add.u32 db, da, 1024; setp.gt.u32 pw, n, %167; selp.b32 db, dv, db, pw; add.u32 dv, dv, 1280;\n"
    "wgmma.fence.sync.aligned;\n"
    "add.u32 t, da, 0; add.u32 u, db, 0;\n"
    "mov.b64 dA, {t, hb}; mov.b64 dB, {u, hb};\n"
    "wgmma.mma_async.sync.aligned.m64n160k16.f32.bf16.bf16 {%0,%1,%2,%3,%4,%5,%6,%7,%8,%9,%10,%11,%12,%13,%14,%15,%16,%17,%18,%19,%20,%21,%22,%23,%24,%25,%26,%27,%28,%29,%30,%31,%32,%33,%34,%35,%36,%37,%38,%39,%40,%41,%42,%43,%44,%45,%46,%47,%48,%49,%50,%51,%52,%53,%54,%55,%56,%57,%58,%59,%60,%61,%62,%63,%64,%65,%66,%67,%68,%69,%70,%71,%72,%73,%74,%75,%76,%77,%78,%79}, dA, dB, ps, 1, 1, 0, 0;\n"
    "add.u32 t, da, 512; add.u32 u, db, 0;\n"
    "mov.b64 dA, {t, hb}; mov.b64 dB, {u, hb};\n"
    "wgmma.mma_async.sync.aligned.m64n160k16.f32.bf16.bf16 {%80,%81,%82,%83,%84,%85,%86,%87,%88,%89,%90,%91,%92,%93,%94,%95,%96,%97,%98,%99,%100,%101,%102,%103,%104,%105,%106,%107,%108,%109,%110,%111,%112,%113,%114,%115,%116,%117,%118,%119,%120,%121,%122,%123,%124,%125,%126,%127,%128,%129,%130,%131,%132,%133,%134,%135,%136,%137,%138,%139,%140,%141,%142,%143,%144,%145,%146,%147,%148,%149,%150,%151,%152,%153,%154,%155,%156,%157,%158,%159}, dA, dB, ps, 1, 1, 0, 0;\n"
    "wgmma.commit_group.sync.aligned;\n"
    "wgmma.wait_group.sync.aligned 1;\n"
    "@pe mbarrier.arrive.shared::cta.b64 _, [pa];\n"
    "add.u32 pa, s8, %163;\n"
    "add.u32 t, da, 2; add.u32 u, db, 2;\n"
    "mov.b64 dA, {t, hb}; mov.b64 dB, {u, hb};\n"
    "wgmma.mma_async.sync.aligned.m64n160k16.f32.bf16.bf16 {%0,%1,%2,%3,%4,%5,%6,%7,%8,%9,%10,%11,%12,%13,%14,%15,%16,%17,%18,%19,%20,%21,%22,%23,%24,%25,%26,%27,%28,%29,%30,%31,%32,%33,%34,%35,%36,%37,%38,%39,%40,%41,%42,%43,%44,%45,%46,%47,%48,%49,%50,%51,%52,%53,%54,%55,%56,%57,%58,%59,%60,%61,%62,%63,%64,%65,%66,%67,%68,%69,%70,%71,%72,%73,%74,%75,%76,%77,%78,%79}, dA, dB, pt, 1, 1, 0, 0;\n"
    "add.u32 t, da, 514; add.u32 u, db, 2;\n"
    "mov.b64 dA, {t, hb}; mov.b64 dB, {u, hb};\n"
    "wgmma.mma_async.sync.aligned.m64n160k16.f32.bf16.bf16 {%80,%81,%82,%83,%84,%85,%86,%87,%88,%89,%90,%91,%92,%93,%94,%95,%96,%97,%98,%99,%100,%101,%102,%103,%104,%105,%106,%107,%108,%109,%110,%111,%112,%113,%114,%115,%116,%117,%118,%119,%120,%121,%122,%123,%124,%125,%126,%127,%128,%129,%130,%131,%132,%133,%134,%135,%136,%137,%138,%139,%140,%141,%142,%143,%144,%145,%146,%147,%148,%149,%150,%151,%152,%153,%154,%155,%156,%157,%158,%159}, dA, dB, pt, 1, 1, 0, 0;\n"
    "add.u32 t, da, 4; add.u32 u, db, 4;\n"
    "mov.b64 dA, {t, hb}; mov.b64 dB, {u, hb};\n"
    "wgmma.mma_async.sync.aligned.m64n160k16.f32.bf16.bf16 {%0,%1,%2,%3,%4,%5,%6,%7,%8,%9,%10,%11,%12,%13,%14,%15,%16,%17,%18,%19,%20,%21,%22,%23,%24,%25,%26,%27,%28,%29,%30,%31,%32,%33,%34,%35,%36,%37,%38,%39,%40,%41,%42,%43,%44,%45,%46,%47,%48,%49,%50,%51,%52,%53,%54,%55,%56,%57,%58,%59,%60,%61,%62,%63,%64,%65,%66,%67,%68,%69,%70,%71,%72,%73,%74,%75,%76,%77,%78,%79}, dA, dB, pt, 1, 1, 0, 0;\n"
    "add.u32 s8, s8, 8; setp.eq.b32 pw, s8, 40; @pw mov.b32 s8, 0; @pw mov.b32 ph, 1; sub.u32 n, n, 1; setp.eq.b32 ps, 0, 0;\n"
    "add.u32 t, da, 516; add.u32 u, db, 4;\n"
    "mov.b64 dA, {t, hb}; mov.b64 dB, {u, hb};\n"
    "wgmma.mma_async.sync.aligned.m64n160k16.f32.bf16.bf16 {%80,%81,%82,%83,%84,%85,%86,%87,%88,%89,%90,%91,%92,%93,%94,%95,%96,%97,%98,%99,%100,%101,%102,%103,%104,%105,%106,%107,%108,%109,%110,%111,%112,%113,%114,%115,%116,%117,%118,%119,%120,%121,%122,%123,%124,%125,%126,%127,%128,%129,%130,%131,%132,%133,%134,%135,%136,%137,%138,%139,%140,%141,%142,%143,%144,%145,%146,%147,%148,%149,%150,%151,%152,%153,%154,%155,%156,%157,%158,%159}, dA, dB, pt, 1, 1, 0, 0;\n"
    "add.u32 t, da, 6; add.u32 u, db, 6;\n"
    "mov.b64 dA, {t, hb}; mov.b64 dB, {u, hb};\n"
    "wgmma.mma_async.sync.aligned.m64n160k16.f32.bf16.bf16 {%0,%1,%2,%3,%4,%5,%6,%7,%8,%9,%10,%11,%12,%13,%14,%15,%16,%17,%18,%19,%20,%21,%22,%23,%24,%25,%26,%27,%28,%29,%30,%31,%32,%33,%34,%35,%36,%37,%38,%39,%40,%41,%42,%43,%44,%45,%46,%47,%48,%49,%50,%51,%52,%53,%54,%55,%56,%57,%58,%59,%60,%61,%62,%63,%64,%65,%66,%67,%68,%69,%70,%71,%72,%73,%74,%75,%76,%77,%78,%79}, dA, dB, pt, 1, 1, 0, 0;\n"
    "add.u32 t, da, 518; add.u32 u, db, 6;\n"
    "mov.b64 dA, {t, hb}; mov.b64 dB, {u, hb};\n"
    "wgmma.mma_async.sync.aligned.m64n160k16.f32.bf16.bf16 {%80,%81,%82,%83,%84,%85,%86,%87,%88,%89,%90,%91,%92,%93,%94,%95,%96,%97,%98,%99,%100,%101,%102,%103,%104,%105,%106,%107,%108,%109,%110,%111,%112,%113,%114,%115,%116,%117,%118,%119,%120,%121,%122,%123,%124,%125,%126,%127,%128,%129,%130,%131,%132,%133,%134,%135,%136,%137,%138,%139,%140,%141,%142,%143,%144,%145,%146,%147,%148,%149,%150,%151,%152,%153,%154,%155,%156,%157,%158,%159}, dA, dB, pt, 1, 1, 0, 0;\n"
    "wgmma.commit_group.sync.aligned;\n"
    "setp.ne.b32 pl, n, %168;\n"
    "@pl bra NOPAUSE;\n"
    "wgmma.wait_group.sync.aligned 0;\n"
    "@pe mbarrier.arrive.shared::cta.b64 _, [%169];\n"
    "W5: mbarrier.try_wait.parity.shared::cta.b64 pw, [%170], 0, 100000;\n"
    "@!pw bra W5;\n"
    "NOPAUSE:\n"
    "setp.ne.b32 pl, n, 0;\n"
    "@pl bra LOOP; }\n"
    : "+f"(d[0]),"+f"(d[1]),"+f"(d[2]),"+f"(d[3]),"+f"(d[4]),"+f"(d[5]),"+f"(d[6]),"+f"(d[7]),"+f"(d[8]),"+f"(d[9]),"+f"(d[10]),"+f"(d[11]),"+f"(d[12]),"+f"(d[13]),"+f"(d[14]),"+f"(d[15]),"+f"(d[16]),"+f"(d[17]),"+f"(d[18]),"+f"(d[19]),"+f"(d[20]),"+f"(d[21]),"+f"(d[22]),"+f"(d[23]),"+f"(d[24]),"+f"(d[25]),"+f"(d[26]),"+f"(d[27]),"+f"(d[28]),"+f"(d[29]),"+f"(d[30]),"+f"(d[31]),"+f"(d[32]),"+f"(d[33]),"+f"(d[34]),"+f"(d[35]),"+f"(d[36]),"+f"(d[37]),"+f"(d[38]),"+f"(d[39]),"+f"(d[40]),"+f"(d[41]),"+f"(d[42]),"+f"(d[43]),"+f"(d[44]),"+f"(d[45]),"+f"(d[46]),"+f"(d[47]),"+f"(d[48]),"+f"(d[49]),"+f"(d[50]),"+f"(d[51]),"+f"(d[52]),"+f"(d[53]),"+f"(d[54]),"+f"(d[55]),"+f"(d[56]),"+f"(d[57]),"+f"(d[58]),"+f"(d[59]),"+f"(d[60]),"+f"(d[61]),"+f"(d[62]),"+f"(d[63]),"+f"(d[64]),"+f"(d[65]),"+f"(d[66]),"+f"(d[67]),"+f"(d[68]),"+f"(d[69]),"+f"(d[70]),"+f"(d[71]),"+f"(d[72]),"+f"(d[73]),"+f"(d[74]),"+f"(d[75]),"+f"(d[76]),"+f"(d[77]),"+f"(d[78]),"+f"(d[79]),"+f"(e[0]),"+f"(e[1]),"+f"(e[2]),"+f"(e[3]),"+f"(e[4]),"+f"(e[5]),"+f"(e[6]),"+f"(e[7]),"+f"(e[8]),"+f"(e[9]),"+f"(e[10]),"+f"(e[11]),"+f"(e[12]),"+f"(e[13]),"+f"(e[14]),"+f"(e[15]),"+f"(e[16]),"+f"(e[17]),"+f"(e[18]),"+f"(e[19]),"+f"(e[20]),"+f"(e[21]),"+f"(e[22]),"+f"(e[23]),"+f"(e[24]),"+f"(e[25]),"+f"(e[26]),"+f"(e[27]),"+f"(e[28]),"+f"(e[29]),"+f"(e[30]),"+f"(e[31]),"+f"(e[32]),"+f"(e[33]),"+f"(e[34]),"+f"(e[35]),"+f"(e[36]),"+f"(e[37]),"+f"(e[38]),"+f"(e[39]),"+f"(e[40]),"+f"(e[41]),"+f"(e[42]),"+f"(e[43]),"+f"(e[44]),"+f"(e[45]),"+f"(e[46]),"+f"(e[47]),"+f"(e[48]),"+f"(e[49]),"+f"(e[50]),"+f"(e[51]),"+f"(e[52]),"+f"(e[53]),"+f"(e[54]),"+f"(e[55]),"+f"(e[56]),"+f"(e[57]),"+f"(e[58]),"+f"(e[59]),"+f"(e[60]),"+f"(e[61]),"+f"(e[62]),"+f"(e[63]),"+f"(e[64]),"+f"(e[65]),"+f"(e[66]),"+f"(e[67]),"+f"(e[68]),"+f"(e[69]),"+f"(e[70]),"+f"(e[71]),"+f"(e[72]),"+f"(e[73]),"+f"(e[74]),"+f"(e[75]),"+f"(e[76]),"+f"(e[77]),"+f"(e[78]),"+f"(e[79])
    : "r"(sc), "n"(desc_lo(B_RING, 16)), "n"(BAR_FULL), "n"(BAR_EMPTY), "n"(BAR_DUMMY), "n"(kHiSw128), "n"(desc_lo(B_STG, 16)),
      "r"(own ? 8 : 10), "r"(pause ? 10 - B_PS : -1), "r"(pa), "r"(pb)
    : "memory");
}

__device__ __forceinline__ void mbar_init(uint32_t bar, uint32_t cnt) { asm volatile("mbarrier.init.shared::cta.b64 [%0], %1;" ::"r"(bar), "r"(cnt) : "memory"); }
__device__ __forceinline__ void mbar_expect(uint32_t bar, uint32_t bytes) { asm volatile("{ .reg .pred e; elect.sync _|e, 0xffffffff;\n@e mbarrier.arrive.expect_tx.shared::cta.b64 _, [%0], %1; }" ::"r"(bar), "r"(bytes) : "memory"); }
__device__ __forceinline__ void mbar_arrive1(uint32_t bar) { asm volatile("{ .reg .pred e; elect.sync _|e, 0xffffffff;\n@e mbarrier.arrive.shared::cta.b64 _, [%0]; }" ::"r"(bar) : "memory"); }
__device__ __forceinline__ void mbar_arrive(uint32_t bar) { asm volatile("mbarrier.arrive.shared::cta.b64 _, [%0];" ::"r"(bar) : "memory"); }
__device__ __forceinline__ void mbar_wait(uint32_t bar, uint32_t parity) {
  asm volatile("{ .reg .pred p;\nLAB_WAIT: mbarrier.try_wait.parity.shared::cta.b64 p, [%0], %1, 100000;\n@!p bra LAB_WAIT; }" ::"r"(bar), "r"(parity) : "memory");
}
__device__ __forceinline__ void wg_bar(int wg) { asm volatile("bar.sync %0, 128;" ::"r"(wg + 1) : "memory"); }
__device__ __forceinline__ void fence_async_smem() { asm volatile("fence.proxy.async.shared::cta;" ::: "memory"); }

__device__ __forceinline__ void tma2d(uint32_t dst, const CUtensorMap* m, int c0, int c1, uint32_t bar) {
  asm volatile("{ .reg .pred e; elect.sync _|e, 0xffffffff;\n@e cp.async.bulk.tensor.2d.shared::cluster.global.mbarrier::complete_tx::bytes [%0], [%1, {%3,%4}], [%2]; }" ::"r"(dst), "l"(m), "r"(bar), "r"(c0), "r"(c1) : "memory");
}
__device__ __forceinline__ void tma3d(uint32_t dst, const CUtensorMap* m, int c0, int c1, int c2, uint32_t bar) {
  asm volatile("{ .reg .pred e; elect.sync _|e, 0xffffffff;\n@e cp.async.bulk.tensor.3d.shared::cluster.global.mbarrier::complete_tx::bytes [%0], [%1, {%3,%4,%5}], [%2]; }" ::"r"(dst), "l"(m), "r"(bar), "r"(c0), "r"(c1), "r"(c2) : "memory");
}
__device__ __forceinline__ void tma5d(uint32_t dst, const CUtensorMap* m, int c0, int c1, int c2, int c3, int c4, uint32_t bar) {
  asm volatile("{ .reg .pred e; elect.sync _|e, 0xffffffff;\n@e cp.async.bulk.tensor.5d.shared::cluster.global.mbarrier::complete_tx::bytes [%0], [%1, {%3,%4,%5,%6,%7}], [%2]; }" ::"r"(dst), "l"(m), "r"(bar), "r"(c0), "r"(c1), "r"(c2), "r"(c3), "r"(c4) : "memory");
}
__device__ __forceinline__ void prefetch3d(const CUtensorMap* m, int c0, int c1, int c2) {
  asm volatile("{ .reg .pred e; elect.sync _|e, 0xffffffff;\n@e cp.async.bulk.prefetch.tensor.3d.L2.global [%0, {%1,%2,%3}]; }" ::"l"(m), "r"(c0), "r"(c1), "r"(c2) : "memory");
}
__device__ __forceinline__ void prefetch_l2(const void* p, uint32_t bytes) {
  asm volatile("{ .reg .pred e; elect.sync _|e, 0xffffffff;\n@e cp.async.bulk.prefetch.L2.global [%0], %1; }" ::"l"(p), "r"(bytes) : "memory");
}
__device__ __forceinline__ void bulk_load(uint32_t dst, const void* src, uint32_t bytes, uint32_t bar) {
  asm volatile("{ .reg .pred e; elect.sync _|e, 0xffffffff;\n@e cp.async.bulk.shared::cluster.global.mbarrier::complete_tx::bytes [%0], [%1], %2, [%3]; }" ::"r"(dst), "l"(src), "r"(bytes), "r"(bar) : "memory");
}
__device__ __forceinline__ void bulk_store(void* dst, uint32_t src, uint32_t bytes) {
  asm volatile("{ .reg .pred e; elect.sync _|e, 0xffffffff;\n@e cp.async.bulk.global.shared::cta.bulk_group [%0], [%1], %2; }" ::"l"(dst), "r"(src), "r"(bytes) : "memory");
}
__device__ __forceinline__ void bulk_reduce(float* dst, uint32_t src, uint32_t bytes) {
  asm volatile("{ .reg .pred e; elect.sync _|e, 0xffffffff;\n@e cp.reduce.async.bulk.global.shared::cta.bulk_group.add.f32 [%0], [%1], %2; }" ::"l"(dst), "r"(src), "r"(bytes) : "memory");
}
__device__ __forceinline__ void bulk_wait() { asm volatile("cp.async.bulk.commit_group;\ncp.async.bulk.wait_group 0;" ::: "memory"); }
__device__ __forceinline__ unsigned load_epoch_raw(const Params& P) {
  unsigned v;
  asm volatile("ld.global.cg.u32 %0, [%1];" : "=r"(v) : "l"(P.s->ep + blockIdx.x * 32) : "memory");
  return v;
}
__device__ __forceinline__ unsigned load_epoch(const Params& P) { return __shfl_sync(~0u, load_epoch_raw(P) + 1, 0); }
__device__ __forceinline__ void pace(uint32_t t0, uint32_t dt) { while ((uint32_t)clock() - t0 < dt) {} }
__device__ __forceinline__ void paced_store(unsigned char* dst, uint32_t src, uint32_t piece, int n, uint32_t dt) {
  const uint32_t c0 = clock();
#pragma unroll 1
  for (int i = 0; i < n; i++) {
    pace(c0, i * dt);
    bulk_store(dst + i * piece, src + i * piece, piece);
  }
}
__device__ __forceinline__ void cnt_add(const Params& P, int idx) {
  asm volatile("{ .reg .pred e; elect.sync _|e, 0xffffffff;\n@e red.release.gpu.global.add.u32 [%0], 1; }" ::"l"(P.s->cnt + idx * 32) : "memory");
}
__device__ __forceinline__ void cnt_wait(const Params& P, int idx, unsigned target) {
  asm volatile("{ .reg .pred p; .reg .s32 v;\nLAB_POLL: ld.relaxed.gpu.global.s32 v, [%0];\nsub.s32 v, v, %1; setp.lt.s32 p, v, 0;\n@p bra LAB_POLL; }" ::"l"(P.s->cnt + idx * 32), "r"(target) : "memory");
}

__device__ __forceinline__ uint32_t pack2(float lo, float hi) {
  uint32_t r;
  asm("cvt.rn.bf16x2.f32 %0, %1, %2;" : "=r"(r) : "f"(hi), "f"(lo));
  return r;
}
__device__ __forceinline__ float ex2(float x) { float r; asm("ex2.approx.ftz.f32 %0, %1;" : "=f"(r) : "f"(x)); return r; }
__device__ __forceinline__ float rcp(float x) { float r; asm("rcp.approx.ftz.f32 %0, %1;" : "=f"(r) : "f"(x)); return r; }
__device__ __forceinline__ void sts128(uint32_t a, uint32_t x, uint32_t y, uint32_t z, uint32_t w) {
  asm volatile("st.shared.v4.b32 [%0], {%1,%2,%3,%4};" ::"r"(a), "r"(x), "r"(y), "r"(z), "r"(w) : "memory");
}
__device__ __forceinline__ void lds128(uint32_t a, uint32_t* r) {
  asm volatile("ld.shared.v4.b32 {%0,%1,%2,%3}, [%4];" : "=r"(r[0]), "=r"(r[1]), "=r"(r[2]), "=r"(r[3]) : "r"(a) : "memory");
}
__device__ __forceinline__ void ldsm4(uint32_t a, uint32_t* r) {
  asm volatile("ldmatrix.sync.aligned.m8n8.x4.shared.b16 {%0,%1,%2,%3}, [%4];" : "=r"(r[0]), "=r"(r[1]), "=r"(r[2]), "=r"(r[3]) : "r"(a) : "memory");
}
__device__ __forceinline__ void ldsm4t(uint32_t a, uint32_t* r) {
  asm volatile("ldmatrix.sync.aligned.m8n8.x4.trans.shared.b16 {%0,%1,%2,%3}, [%4];" : "=r"(r[0]), "=r"(r[1]), "=r"(r[2]), "=r"(r[3]) : "r"(a) : "memory");
}
__device__ __forceinline__ void stsm4(uint32_t a, uint32_t x, uint32_t y, uint32_t z, uint32_t w) {
  asm volatile("stmatrix.sync.aligned.m8n8.x4.shared.b16 [%0], {%1,%2,%3,%4};" ::"r"(a), "r"(x), "r"(y), "r"(z), "r"(w) : "memory");
}
__device__ __forceinline__ void stsm2(uint32_t a, uint32_t x, uint32_t y) {
  asm volatile("stmatrix.sync.aligned.m8n8.x2.shared.b16 [%0], {%1,%2};" ::"r"(a), "r"(x), "r"(y) : "memory");
}
__device__ __forceinline__ void stsm4t(uint32_t a, uint32_t x, uint32_t y, uint32_t z, uint32_t w) {
  asm volatile("stmatrix.sync.aligned.m8n8.x4.trans.shared.b16 [%0], {%1,%2,%3,%4};" ::"r"(a), "r"(x), "r"(y), "r"(z), "r"(w) : "memory");
}
__device__ __forceinline__ void mma16(float* d, uint32_t a0, uint32_t a1, uint32_t a2, uint32_t a3, uint32_t b0, uint32_t b1) {
  asm("mma.sync.aligned.m16n8k16.row.col.f32.bf16.bf16.f32 {%0,%1,%2,%3},{%4,%5,%6,%7},{%8,%9},{%0,%1,%2,%3};"
      : "+f"(d[0]), "+f"(d[1]), "+f"(d[2]), "+f"(d[3]) : "r"(a0), "r"(a1), "r"(a2), "r"(a3), "r"(b0), "r"(b1));
}
__device__ __forceinline__ void mma8(float* d, uint32_t a0, uint32_t a1, uint32_t b0) {
  asm("mma.sync.aligned.m16n8k8.row.col.f32.bf16.bf16.f32 {%0,%1,%2,%3},{%4,%5},{%6},{%0,%1,%2,%3};"
      : "+f"(d[0]), "+f"(d[1]), "+f"(d[2]), "+f"(d[3]) : "r"(a0), "r"(a1), "r"(b0));
}
__device__ __forceinline__ float bf_lo(uint32_t v) { return __uint_as_float(v << 16); }
__device__ __forceinline__ float bf_hi(uint32_t v) { return __uint_as_float(v & 0xffff0000u); }
__device__ __forceinline__ float ldbf(const __nv_bfloat16* p) { return __bfloat162float(__ldg(p)); }

#define V_LAG 1
#define RED_B 2560
#define KV_PF 0
#define NUM_PF 0
#define O_S1 0
#define XLA 1
#define A_PF 3
#define P_PACE0 1500
#define P_PACE 500
#define H_N 20
#define H_PACE 150
#define O_N 1
#define O_PACE 200
#define RED_PACE1 RED_PACE
#define O_S2 6
#define B_SPLIT 1
#define B_HOLD 0
#define SM_PK
#define MAP 0
#define NUM_U 4
#define RED_N 20
#define RED_PACE 220
#define A_SLEEP 0
#define B_SLEEP 100
#define A_PACE 300
#define B_PACE 600
#define B_PACE0 600
__device__ __forceinline__ void a_producer(const Params& P, int rb, int half, long long t_start) {
  const uint32_t c0 = clock();
#pragma unroll 1
  for (int n = 1; n < 20; n++) {
    const int s = n % A_NS, kb = n < 2 * XLA ? n : (n >> 1) + XLA;
    if (n < A_NS) pace(c0, (n - 1) * A_PACE);
    if ((n < 2 * XLA || !(n & 1)) && kb < 10) {
      mbar_expect(BAR_X + 8 * kb, 8192);
      tma2d(A_X + kb * 8192, &P.xa, kb * 64, rb * 64, BAR_X + 8 * kb);
    }
    mbar_wait(BAR_EMPTY + 8 * s, ((n / A_NS) & 1) ^ 1);
    ST(n);
    mbar_expect(BAR_FULL + 8 * s, kBlob);
    tma3d(A_RING + s * kBlob, &P.wv, 0, n * 32, 20 + 5 * half, BAR_FULL + 8 * s);
    if (n == A_PF && rb >= A_NS && rb < 20) prefetch3d(&P.wv, 0, rb * 32, 20 + 5 * half);
  }
  TS1(40);
  int n = 20;
#pragma unroll 1
  for (int task = 0; task < 8; task++) {
    const int slot = min(task >> 1, 2) * 4 + 2 * half + (~task & 1);
    if (task < 6 && !(task & 1)) mbar_wait(BAR_W + 4 * task, 0);
    if (task == 0) TS1(41);
    const unsigned char* src = P.s->w + (size_t)(slot * 10 + (task == 6 ? O_S1 : task == 7 ? O_S2 : 0)) * kBlob;
    const int end = n + (task < 4 ? 10 : task == 4 ? O_S1 : task == 5 ? O_S2 : task == 6 ? 10 - O_S1 : 10 - O_S2);
    const uint32_t bytes = task < 4 ? kFold : kBlob;
#pragma unroll 1
    for (; n < end; n++, src += kBlob) {
      const int s = n % A_NS;
      mbar_wait(BAR_EMPTY + 8 * s, ((n / A_NS) & 1) ^ 1);
      ST(n);
      mbar_expect(BAR_FULL + 8 * s, bytes);
      bulk_load(A_RING + s * kBlob, src, bytes, BAR_FULL + 8 * s);
      if (n == 53 + A_NS) mbar_arrive1(BAR_KV0);
    }
  }
}

__device__ __forceinline__ void a_poller(const Params& P, int half, unsigned ep) {
#pragma unroll 1
  for (int i = 0; i < 6; i++) {
    cnt_wait(P, C_W + (i >> 1) * 4 + 2 * half + (i & 1), ep * 10);
    if (i & 1) mbar_arrive1(BAR_W + 8 * (i >> 1));
  }
}

__device__ __forceinline__ void a_helper(const Params& P, int rb, int half, long long t_start) {
  const unsigned ep = load_epoch(P);
#pragma unroll 1
  for (int ty = 0; ty < 2; ty++) {
    const int hg = 2 * half + (ty ^ 1);
    mbar_wait(BAR_RED + 8 * ty, 0);
    const uint32_t c0 = clock();
    float* dst = P.s->kv + hg * 6720;
    constexpr int NP = 20480 / RED_B;
#pragma unroll 1
    for (int i = 0; i < NP; i++) {
      const int j = (i + rb) & (NP - 1);
      pace(c0, i * (ty ? RED_PACE1 : RED_PACE));
      bulk_reduce(dst + 1600 + j * (RED_B / 4), A_PHI + kHalf + j * RED_B + (j / (NP / 4)) * 32, RED_B);
    }
    asm volatile("cp.async.bulk.commit_group;" ::: "memory");
    pace(c0, NP * (ty ? RED_PACE1 : RED_PACE));
    bulk_reduce(dst, A_Z, 6400);
    asm volatile("cp.async.bulk.commit_group;\ncp.async.bulk.wait_group.read 1;" ::: "memory");
    mbar_arrive1(ty ? BAR_STG1 : BAR_STG);
    TS1(50 + 3 * ty);
    bulk_wait();
    if (ty == 0) mbar_arrive1(BAR_PREP);
    cnt_add(P, C_KV + hg);
    TS1(52 + 3 * ty);
  }
  mbar_expect(BAR_KVR + 8, kKvBytes);
  cnt_wait(P, C_KV + 2 * half, ep * 32);
  TS1(43);
  mbar_wait(BAR_QD, 0);
  bulk_load(A_X + 3 * kBlob, P.s->kv + 2 * half * 6720 + 1600, kBlob, BAR_KVR + 8);
  bulk_load(A_Z, P.s->kv + 2 * half * 6720, 6400, BAR_KVR + 8);
}

__device__ __forceinline__ void a_exchange(const Params& P, int rb, int half, unsigned ep, long long t_start) {
  mbar_expect(BAR_KVR, kKvBytes);
  cnt_wait(P, C_KV + 2 * half + 1, ep * 32);
  TS1(42);
  mbar_wait(BAR_KV0, 0);
  bulk_load(A_X, P.s->kv + (2 * half + 1) * 6720, kKvBytes, BAR_KVR);
  mbar_wait(BAR_QD, 0);
#pragma unroll 1
  for (int ty = 0; ty < 2; ty++) {
    const int me = rb * 4 + 2 * half + ty;
    const uint32_t reg = A_X + ty * kBlob;
    mbar_expect(BAR_P + 24 * ty, kBlob);
    mbar_wait(BAR_O + 8 * ty, 0);
    paced_store(P.s->ox + (size_t)me * kBlob, reg, kBlob / O_N, O_N, O_PACE);
    bulk_wait();
    cnt_add(P, C_O + me);
    cnt_wait(P, C_O + (me ^ 2), ep);
    bulk_load(reg + 2 * kBlob, P.s->ox + (size_t)(me ^ 2) * kBlob, kBlob, BAR_P + 24 * ty);
    TS1(44 + ty);
  }
}

template <int WG>
__device__ __forceinline__ void a_vgemm(float* v, int lane, long long t_start) {
#pragma unroll 1
  for (int n = 0; n < 20; n++) {
    const int s = n % A_NS;
    mbar_wait(BAR_X + 8 * (n >> 1), 0);
    mbar_wait(BAR_FULL + 8 * s, (n / A_NS) & 1);
    if (n == 0) TS(0 + 16 * WG);
    const uint32_t da = desc_lo(A_X, 16) + (n >> 1) * 512 + (n & 1) * 4;
    const uint32_t db = desc_lo(A_RING, 4096) + s * (kBlob >> 4) + (WG ? 0 : 768);
    wg_fence();
    if (WG == 0) {
      wgmma_n128<1>(v, mkdesc(da, kHiSw128), mkdesc(db, kHiSw128), n);
      wgmma_n128<1>(v, mkdesc(da + 2, kHiSw128), mkdesc(db + 128, kHiSw128), 1);
    } else {
      wgmma_n192<1>(v, mkdesc(da, kHiSw128), mkdesc(db, kHiSw128), n);
      wgmma_n192<1>(v, mkdesc(da + 2, kHiSw128), mkdesc(db + 128, kHiSw128), 1);
    }
    wg_commit();
    wg_wait<1>();
    if (n) mbar_arrive1(BAR_EMPTY + 8 * (s ? s - 1 : A_NS - 1));
  }
  wg_wait<0>();
}

constexpr float kL = 1.4426950408889634f;
__device__ __forceinline__ void softmax_stats(const float* p, float& mx, float& mn) {
  int x[2];
  unsigned n[2];
#pragma unroll
  for (int i = 0; i < 2; i++) {
    const float* a = p + 36 * i;
    x[i] = __vimax3_s32(__float_as_int(a[0]), __float_as_int(a[4]), __float_as_int(a[8]));
    n[i] = __vimax3_u32(__float_as_uint(a[0]), __float_as_uint(a[4]), __float_as_uint(a[8]));
#pragma unroll
    for (int j = 3; j < 9; j += 2) {
      x[i] = __vimax3_s32(x[i], __float_as_int(a[4 * j]), __float_as_int(a[4 * j + 4]));
      n[i] = __vimax3_u32(n[i], __float_as_uint(a[4 * j]), __float_as_uint(a[4 * j + 4]));
    }
  }
  mx = -kL * __int_as_float(__vimax3_s32_relu(x[0], x[1], __float_as_int(p[72])));
  mn = kL * fminf(__uint_as_float(__vimax3_u32(n[0], n[1], __float_as_uint(p[72]))), 0.f);
}
__device__ __forceinline__ void softmax_group(const float* p, float mx, float mn, uint32_t a) {
  float t[40];
  t[0] = ex2(mx);
  t[20] = ex2(mn);
#pragma unroll
  for (int j = 0; j < 19; j++) t[1 + j] = ex2(fmaf(p[4 * j], kL, mx));
#pragma unroll
  for (int j = 0; j < 19; j++) t[21 + j] = ex2(fmaf(p[4 * j], -kL, mn));
  float s[4];
#pragma unroll
  for (int i = 0; i < 4; i++) s[i] = t[10 * i] + t[10 * i + 1];
#pragma unroll
  for (int j = 2; j < 10; j++)
#pragma unroll
    for (int i = 0; i < 4; i++) s[i] += t[10 * i + j];
  const float rp = rcp(s[0] + s[1]), rn = rcp(s[2] + s[3]);
  uint32_t k[20];
  const uint32_t p2 = pack2(rp, rp), n2 = pack2(rn, rn);
#pragma unroll
  for (int j = 0; j < 20; j++) asm("mul.rn.bf16x2 %0, %1, %2;" : "=r"(k[j]) : "r"(pack2(t[2 * j], t[2 * j + 1])), "r"(j < 10 ? p2 : n2));
#pragma unroll
  for (int c = 0; c < 5; c++) sts128(a + c * 512, k[4 * c], k[4 * c + 1], k[4 * c + 2], k[4 * c + 3]);
}

__device__ __forceinline__ void a_consumer(const Params& P, int rb, int half, int wg, long long t_start) {
  const int tid = threadIdx.x & 127, w = tid >> 5, lane = tid & 31, gi = lane >> 2, q = lane & 3;
  const int hg = 2 * half + (wg ^ 1);
  uint32_t hold[40];
  {
    float v[96];
    reg_fence<96>(v);
    if (wg == 0) a_vgemm<0>(v, lane, t_start);
    else a_vgemm<1>(v, lane, t_start);
    reg_fence<96>(v);
    mbar_arrive1(BAR_EMPTY + 32);
    TS(1 + 16 * wg);
    const uint32_t vst = A_PHI + (wg ? 0 : 24576) + (lane >> 4) * 1024 + (16 * w + (lane & 15)) * 16;
#pragma unroll
    for (int cc = 0; cc < 12; cc++) {
      const int c = (cc + 10) % 12;
      if (c < 8 || wg)
        stsm4(vst + c * 2048, pack2(v[8 * c], v[8 * c + 1]), pack2(v[8 * c + 2], v[8 * c + 3]), pack2(v[8 * c + 4], v[8 * c + 5]), pack2(v[8 * c + 6], v[8 * c + 7]));
      if (cc == 1 && wg) {
        asm volatile("bar.arrive 3, 256;" ::: "memory");
        if (V_LAG) asm volatile("bar.sync 4, 256;" ::: "memory");
      }
    }
    if (wg) wg_bar(1);
    else asm volatile("bar.sync 3, 256;" ::: "memory");
    const uint32_t vb = A_PHI + (wg ? 0 : 20480) + w * 5120;
    const uint32_t va = vb + ((lane >> 3) & 1) * 1024 + ((lane & 7) + 8 * (lane >> 4)) * 16;
#pragma unroll
    for (int ks = 0; ks < 4; ks++) {
      ldsm4t(va + ks * 256, hold + 4 * ks);
      ldsm4t(va + 3072 + ks * 256, hold + 16 + 4 * ks);
    }
    ldsm4t(vb + 2048 + lane * 16, hold + 32);
    ldsm4t(vb + 2560 + lane * 16, hold + 36);
    if (V_LAG && wg == 0) asm volatile("bar.arrive 4, 256;" ::: "memory");
    mbar_arrive1(BAR_V);
  }
  const uint32_t pf = A_PHI + ((lane >> 3) & 1) * kHalf + w * kPair + (lane >> 4) * 512 + (lane & 7) * 16;
  float acc[80];
  reg_kill<80>(acc);
#pragma unroll 1
  for (int tk = 0; tk < 2; tk++) {
    const int task = uniform(tk);
    if (task == 0) {
      mbar_wait(BAR_TOK + 8 * wg, 0);
    } else {
      uint32_t b[4][20];
#pragma unroll
      for (int i = 0; i < 5 * KV_PF; i++) ldsm4t(pf + (i % 5) * 1024 + (i / 5) * 128, b[i / 5] + 4 * (i % 5));
      mbar_wait(BAR_TOK + 8 * wg, 1);
      TS(5 + 16 * wg);
#pragma unroll
      for (int i = 0; i < 80; i++) acc[i] = 0.f;
      constexpr int LA = KV_PF ? KV_PF : 1;
#pragma unroll
      for (int ks = KV_PF ? 0 : -1; ks < 4; ks++)
#pragma unroll
        for (int cp = 0; cp < 5; cp++) {
          if (ks + LA < 4) ldsm4t(pf + cp * 1024 + (ks + LA) * 128, b[ks + LA] + 4 * cp);
          if (ks + LA == 3 && cp == 4) mbar_arrive1(BAR_FREE + 8 * wg);
          if (ks >= 0) {
#pragma unroll
            for (int c = 2 * cp; c < 2 * cp + 2; c++) {
              const uint32_t* a = hold + (c < 5 ? 0 : 16) + 4 * ks;
              mma16(acc + 8 * c, a[0], a[1], a[2], a[3], b[ks][2 * c], b[ks][2 * c + 1]);
              mma16(acc + 8 * c + 4, hold[32 + 2 * ks], 0x3F803F80u, hold[33 + 2 * ks], 0x3F803F80u, b[ks][2 * c], b[ks][2 * c + 1]);
            }
          }
        }
      TS(46 + 2 * wg);
#pragma unroll
      for (int c = 0; c < 10; c++) {
        const float* x = acc + 8 * c;
        const bool isv = (gi >> 2) == c / 5;
        sts128(A_PHI + kHalf + w * kPair + c * 512 + lane * 16, __float_as_uint(x[0]), __float_as_uint(x[1]), __float_as_uint(x[2]), __float_as_uint(x[3]));
        asm volatile("st.shared.v2.f32 [%0], {%1,%2};" ::"r"(A_Z + w * 1600 + c * 160 + (isv ? gi & 3 : 4) * 32 + q * 8), "f"(isv ? x[4] : x[6]), "f"(isv ? x[5] : x[7]) : "memory");
      }
      fence_async_smem();
      mbar_arrive1(BAR_RED + 8 * wg);
    }
    TS(3 + 3 * task + 16 * wg);
    uint32_t b8 = 0;
    a_mainloop152(acc, b8, desc_lo(A_X, 16), 0, 10, 0, 0);
    mbar_arrive1(BAR_TOK + 8 * (wg ^ 1));
    wg_wait<0>();
    reg_fence<76>(acc);
    if (lane < 2) mbar_arrive(b8);
    if (task & wg) mbar_arrive1(BAR_QD);
    TS(4 + 3 * task + 16 * wg);

    uint32_t pa = A_PHI + q * kPair + (8 * w + gi) * 16;
    uint32_t gate = task ? (wg ? BAR_QF : BAR_FREE + 8) : (wg ? BAR_FREE : BAR_V);
    const uint32_t gate1 = task == wg ? gate : task ? BAR_STG1 : BAR_STG;
    int hh = P.one;
#pragma unroll 1
    do {
      float mx[2], mn[2];
      softmax_stats(acc, mx[0], mn[0]);
      softmax_stats(acc + 1, mx[1], mn[1]);
      mbar_wait(gate, 0);
      softmax_group(acc, mx[0], mn[0], pa);
      softmax_group(acc + 1, mx[1], mn[1], pa + 2560);
      pa += kHalf;
      gate = gate1;
#pragma unroll
      for (int j = 0; j < 19; j++) { acc[4 * j] = acc[4 * j + 2]; acc[4 * j + 1] = acc[4 * j + 3]; }
    } while (hh--);
    TS(56 + task + 2 * wg);
    if (task == 0) {
      if (wg) mbar_wait(BAR_PREP, 0);
    } else {
      mbar_wait(BAR_KVR + 8 * wg, 0);
      const uint32_t kz = (wg ? A_Z : A_X) + w * 1600 + q * 8, k4 = A_X + (wg ? 3 * kBlob : 6400) + w * 5120 + lane * 16;
#pragma unroll
      for (int c = 0; c < 10; c++) {
        const int h2 = c / 5, i = (c + 4 * h2) % 5, st = i < 4 ? 4 : 1, o = 16 * h2 + (i < 4 ? i : 12);
        uint32_t x[4];
        float z0, z1;
        lds128(k4 + c * 512, x);
        asm volatile("ld.shared.v2.f32 {%0,%1}, [%2];" : "=f"(z0), "=f"(z1) : "r"(kz + c * 160 + ((gi >> 2) == h2 ? gi & 3 : 4) * 32) : "memory");
        hold[o] = pack2(__uint_as_float(x[0]), __uint_as_float(x[1]));
        hold[o + st] = pack2(__uint_as_float(x[2]), __uint_as_float(x[3]));
        hold[o + 2 * st] = pack2(z0, z1);
      }
    }
    reg_kill<80>(acc);
    wg_bar(wg);
    TS(14 + task + 16 * wg);
  }
  {
    uint32_t aa[4][20];
#pragma unroll
    for (int i = 0; i < 20; i++) {
      if (i == 5 * NUM_PF) { mbar_wait(BAR_TOK + 8 * wg, 0); TS(8 + 16 * wg); }
      ldsm4(pf + ((i + 2) % 5) * 1024 + (i / 5) * 128, aa[i / 5] + 4 * ((i + 2) % 5));
    }
    if (wg == 0) mbar_arrive1(BAR_QF);
    if (O_S1 == 0 && NUM_PF < 4 && wg == 0) mbar_arrive1(BAR_TOK + 8);
    if (NUM_PF == 4) { mbar_wait(BAR_TOK + 8 * wg, 0); TS(8 + 16 * wg); }
    const uint32_t oa = A_X + wg * kBlob + (5 * w + (lane >> 4)) * 1024 + (lane & 15) * 16;
#pragma unroll
    for (int u = 0; u < 4; u++) {
      const uint32_t* a = aa[u];
      float d[2][12];
#pragma unroll
      for (int h2 = 0; h2 < 2; h2++) {
        const uint32_t* b = hold + 16 * h2;
#pragma unroll
        for (int i = 0; i < 12; i++) d[h2][i] = 0.f;
        const uint32_t* a8 = a + 8 + 2 * h2;
        const uint32_t* a16 = a + 12 * h2;
#pragma unroll
        for (int j = 2; j >= 0; j--) {
          mma8(d[h2] + 4 * j, a8[0], a8[1], b[12 + j]);
          mma16(d[h2] + 4 * j, a16[0], a16[1], a16[2], a16[3], b[4 * j], b[4 * j + 1]);
          mma16(d[h2] + 4 * j, a16[4], a16[5], a16[6], a16[7], b[4 * j + 2], b[4 * j + 3]);
        }
      }
      uint32_t o[10];
#pragma unroll
      for (int hh = 0; hh < 2; hh++) {
        const bool up = q & 2;
        const float r0 = rcp((up ? d[0][8 + 2 * hh] : d[1][8 + 2 * hh]) + 1e-6f);
        const float r1 = __shfl_xor_sync(~0u, r0, 2);
        const float ra = up ? r0 : r1, rb2 = up ? r1 : r0;
        o[0 + hh] = pack2(d[0][2 * hh] * ra, d[0][2 * hh + 1] * ra);
        o[2 + hh] = pack2(d[0][4 + 2 * hh] * ra, d[0][5 + 2 * hh] * ra);
        o[4 + hh] = pack2((up ? d[1][8 + 2 * hh] : d[0][8 + 2 * hh]) * r1, (up ? d[1][9 + 2 * hh] : d[0][9 + 2 * hh]) * r1);
        o[6 + hh] = pack2(d[1][2 * hh] * rb2, d[1][2 * hh + 1] * rb2);
        o[8 + hh] = pack2(d[1][4 + 2 * hh] * rb2, d[1][5 + 2 * hh] * rb2);
      }
      stsm4(oa + u * 256, o[0], o[1], o[2], o[3]);
      stsm4(oa + u * 256 + 2048, o[4], o[5], o[6], o[7]);
      stsm2(oa + u * 256 + 4096, o[8], o[9]);
    }
    fence_async_smem();
    mbar_arrive1(BAR_O + 8 * wg);
#pragma unroll
    for (int i = 0; i < 80; i++) acc[i] = 0.f;
    reg_fence<80>(acc);
    mbar_wait(BAR_O, 0);
  }
#pragma unroll 1
  for (int rr = O_S1 ? 0 : wg ^ 1; rr <= P.one; rr++) {
    const int r = uniform(rr);
    if (r) {
      mbar_wait(BAR_TOK + 8 * wg, 1);
      TS(11 + 16 * wg);
    }
    TS(9 + 3 * r + 16 * wg);
    const int p1 = wg ? O_S2 : O_S1, p0 = r ? p1 : 0, n0 = r ? (wg ? 70 + O_S2 : 60 + O_S1 + O_S2) : 60 + O_S1 * wg;
    uint32_t b8 = 8 * (n0 % A_NS);
    a_mainloop160(acc, b8, desc_lo(A_X, 1024) + p0 * 512, (n0 / A_NS) & 1, r ? 10 - p1 : p1, 1, BAR_V + 8 * p0);
    mbar_arrive1(BAR_TOK + 8 * (wg ^ 1));
    wg_wait<0>();
    reg_fence<80>(acc);
    if (lane < 2) mbar_arrive(b8);
    TS(10 + 3 * r + 16 * wg);
  }
  float* o = P.out + (size_t)(rb * 64 + 16 * w + gi) * 1280 + 160 * hg + 4 * q;
#pragma unroll
  for (int jp = 0; jp < 10; jp++) {
#pragma unroll
    for (int hh = 0; hh < 2; hh++)
      *reinterpret_cast<float4*>(o + hh * 8 * 1280 + 16 * jp) =
          make_float4(acc[8 * jp + 2 * hh], acc[8 * jp + 2 * hh + 1], acc[8 * jp + 4 + 2 * hh], acc[8 * jp + 5 + 2 * hh]);
    if (A_SLEEP && jp < 9) __nanosleep(wg ? 0 : A_SLEEP);
  }
  TS(32 + wg);
}

__device__ __forceinline__ void fold_load(const Params& P, int job, uint32_t buf, uint32_t bar, uint32_t bar_phi) {
  const int grp = job / 10, kb = job - 10 * grp;
  const int col = (grp & 3) * 160 + (grp < 4 ? 640 : 0);
  mbar_expect(bar_phi, kPrepPhi);
  bulk_load(buf + kPrepW, P.wphi + (grp & 3) * 3200, kPrepPhi, bar_phi);
  mbar_expect(bar, kPrepW);
#pragma unroll
  for (int i = 0; i < 3; i++) tma5d(buf + i * 8192, &P.wp, col + i * 64, 0, 0, 0, 2 * kb, bar);
}
__device__ __forceinline__ void wo_load(const Params& P, int job, uint32_t buf, uint32_t bar) {
  const int ns = job / 10, kb = job - 10 * ns;
  mbar_expect(bar, kPrepW);
#pragma unroll 1
  for (int i = 0; i < 6; i++) {
    const int u = 2 * kb + (i & 1), pos = u / 5;
    tma5d(buf + i * 4096, &P.wop, ns * 160 + (i >> 1) * 64, 0, 0, 0, 5 * (2 * (((ns ^ pos) >> 1) & 1) + 1 - (pos & 1) - pos) + u, bar);
  }
}

__device__ __forceinline__ void prep_fold(uint32_t buf, uint32_t bar, uint32_t bar_phi, long long t_start) {
  const int tid = threadIdx.x, hl = tid >> 5, lane = tid & 31, gi = lane >> 2, q = lane & 3;
  const int dq = 2 * q - 4 * (hl & 1);
  const uint32_t wq = buf + kPrepW + hl * 800 + dq * 40, wp = wq + gi * 2 + 2;
  uint32_t fa[12];
  mbar_wait(bar_phi, 0);
#pragma unroll
  for (int dg = 0; dg < 3; dg++)
#pragma unroll
    for (int fg = 0; fg < 4; fg++) {
      uint32_t lo, hi;
      asm volatile("ld.shared.u16 %0, [%2];\nld.shared.u16 %1, [%2+40];" : "=r"(lo), "=r"(hi) : "r"(fg < 3 ? wp + dg * 320 + fg * 16 : wq + dg * 320) : "memory");
      const uint32_t x = __byte_perm(lo, hi, 0x5410);
      fa[4 * dg + fg] = (dg == 1 || (unsigned)(dq + 8 * dg) < 20u) ? x : 0u;
    }
  mbar_wait(bar, 0);
  TS(7 + 16 * (hl >> 2));
  uint32_t b[2][3][4];
#pragma unroll
  for (int dg = 2; dg >= 0; dg--) {
    const int c = ((5 * hl) >> 1) + dg;
    const uint32_t a = buf + (c >> 3) * 8192 + lane * 128 + (((c ^ lane) & 7) << 4);
    ldsm4(a, b[0][dg]);
    ldsm4(a + 4096, b[1][dg]);
  }
  asm volatile("bar.sync 3, 256;" ::: "memory");
#pragma unroll
  for (int th = 0; th < 2; th++) {
    uint32_t r[3][4];
#pragma unroll
    for (int tt = 0; tt < 4; tt++) {
      float d0[4] = {0.f, 0.f, 0.f, 0.f}, d1[4] = {0.f, 0.f, 0.f, 0.f};
      mma8(d0, fa[8], fa[9], b[th][2][tt]);
      mma16(d0, fa[0], fa[1], fa[4], fa[5], b[th][0][tt], b[th][1][tt]);
      mma8(d1, fa[10], fa[11], b[th][2][tt]);
      mma16(d1, fa[2], fa[3], fa[6], fa[7], b[th][0][tt], b[th][1][tt]);
      r[0][tt] = pack2(d0[0] - d1[2], d0[1] - d1[3]);
      r[1][tt] = pack2(d0[2] - d1[2], d0[3] - d1[3]);
      r[2][tt] = pack2(d1[0] - d1[2], d1[1] - d1[3]);
    }
    const uint32_t dst = buf + (8 * gi + hl) * 128 + (((4 * th + q) ^ hl) << 4);
#pragma unroll
    for (int fg = 0; fg < 3; fg++) sts128(dst + fg * 8192, r[fg][0], r[fg][1], r[fg][2], r[fg][3]);
  }
  fence_async_smem();
}

__device__ __forceinline__ void prep_wo(uint32_t buf) {
  const int tid = threadIdx.x & 127, w = tid >> 5, lane = tid & 31, gi = lane >> 2, q = lane & 3;
  const int th = w & 1, c0 = w >> 1;
  uint32_t v[10][4];
#pragma unroll
  for (int i = 0; i < 10; i++)
    ldsm4t(buf + (i >> 2) * 8192 + th * 4096 + lane * 128 + ((((2 * i + c0) ^ lane) & 7) << 4), v[i]);
  wg_bar(1);
  const int row = 4 * (gi & 2) + 4 * c0 + 2 * (gi >> 2) + (gi & 1);
  const uint32_t dst = buf + row * 128 + ((((4 * th + q) ^ row) & 7) << 4);
#pragma unroll
  for (int i = 0; i < 10; i++) sts128(dst + i * 2048, v[i][0], v[i][1], v[i][2], v[i][3]);
  fence_async_smem();
}

__device__ __forceinline__ void b_producer_w(const Params& P, int g, long long t_start) {
  const uint32_t c0 = clock();
#pragma unroll 1
  for (int task = 0; task < 4; task++) {
#pragma unroll 1
    for (int st = 0; st < 10; st++) {
      const int s = st < 5 ? st : st - 5;
      const uint32_t slot = B_RING + s * B_SLOT, full = BAR_FULL + 8 * s;
      if (task == 0 && st < 5) pace(c0, B_PACE0 + st * B_PACE);
      mbar_wait(BAR_EMPTY + 8 * s, st < 5);
      mbar_expect(full, 16384);
      if (task < 2) {
        tma2d(slot, &P.bre, st * 64, g * 128 + task * 64, full);
        tma2d(slot + 8192, &P.bim, st * 64, g * 128 + task * 64, full);
      } else {
        const int i = (st >> 1) - 1, k = (i < 0 ? g : i < g ? i : i + 1) * 128 + (task - 2) * 64;
        tma5d(slot, (st & 1) ? &P.cim : &P.cre, k, 0, 0, 4 * g, 0, full);
      }
    }
  }
}

__device__ __forceinline__ void b_producer_x(const Params& P, int tb, int g, long long t_start) {
  const uint32_t c0 = clock();
  const CUtensorMap* xm = tb < 12 ? &P.xb : &P.xbl;
  const int xj = tb < 12 ? 0 : -4, xb = tb < 12 ? tb : 0;
  unsigned ep = 0;
#pragma unroll 1
  for (int task = 0; task < 4; task++) {
    if (task == 1) ep = load_epoch(P);
    const bool own = task >= 2;
#pragma unroll 1
    for (int st = 0; st < 10; st++) {
      const int s = st < 5 ? st : st - 5;
      const uint32_t slot = B_RING + s * B_SLOT + 16384, full = BAR_FULL + 8 * s;
      if (task == 0 && st < 5) pace(c0, B_PACE0 + st * B_PACE);
      if (own && st == 2) {
        TS1(36 + 2 * task);
        cnt_wait(P, C_H + 2 * tb + task - 2, ep * 5);
        TS1(37 + 2 * task);
      }
      mbar_wait(BAR_EMPTY + 8 * s, st < 5);
      ST(task * 10 + st);
      if (own && st < 2) {
        mbar_arrive1(full);
      } else {
        mbar_expect(full, kBlob);
        const int i = (st >> 1) - 1, gs = i < g ? i : i + 1;
        if (task < 2) tma5d(slot, xm, st * 64, 0, 0, xj, xb, full);
        else bulk_load(slot, P.s->h + (size_t)(tb * 20 + (task - 2) * 10 + 2 * gs + (st & 1)) * kBlob, kBlob, full);
      }
      if (task == 3 && st == 6) {
        mbar_expect(BAR_W, 2 * kBlob);
        tma5d(B_STG, xm, g * 128, 0, 0, xj, xb, BAR_W);
        tma5d(B_STG + kBlob, xm, g * 128 + 64, 0, 0, xj, xb, BAR_W);
      }
    }
  }
}

__device__ __forceinline__ void b_helper(const Params& P, int bi, int tb, int g, long long t_start) {
#pragma unroll 1
  for (int job = bi; job < 120; job += 80) {
    if (job >= 80) wo_load(P, bi, B_STG, BAR_P1);
    mbar_wait(job < 80 ? BAR_PREP : BAR_FREE, 0);
    bulk_store(P.s->w + (size_t)job * kBlob, B_STG, kBlob);
    if (job < 40) bulk_store(P.s->kv + job * 672, B_ZERO, 2688);
    bulk_wait();
    cnt_add(P, C_W + job / 10);
    TS1(job < 80 ? 34 : 35);
  }
  mbar_arrive1(BAR_KVR);
  mbar_wait(BAR_TOK + 8, 0);
  if (bi < 64) {
    prefetch_l2(P.cre_p + bi * 6400, 12800);
    prefetch_l2(P.cim_p + bi * 6400, 12800);
  }
#pragma unroll 1
  for (int ty = 0; ty < 2; ty++) {
    mbar_wait(BAR_O + 8 * ty, 0);
    paced_store(P.s->h + (size_t)(tb * 20 + ty * 10 + 2 * g) * kBlob, B_STG, 2 * kBlob / H_N, H_N, H_PACE);
    bulk_wait();
    mbar_arrive1(BAR_STG);
    TS1(46 + ty);
    cnt_add(P, C_H + 2 * tb + ty);
    TS1(44 + ty);
  }
}

__device__ __forceinline__ void cmul(float ar, float ai, float br, float bi, float& cr, float& ci) {
  const float r = fmaf(ar, br, -ai * bi), i = fmaf(ar, bi, ai * br);
  cr = r; ci = i;
}
__device__ __forceinline__ void cstep(float mr, float mi, float& hr, float& hi, float er, float ei) {
  const float r = fmaf(mr, hr, fmaf(-mi, hi, er)), i = fmaf(mr, hi, fmaf(mi, hr, ei));
  hr = r; hi = i;
}
__device__ __forceinline__ void quad_gather(const float* f, int q, float* o) {
  const bool b0 = q & 1, b1 = q & 2;
  const float mine = b0 ? f[1] : f[0];
  const float r = __shfl_xor_sync(~0u, b0 ? f[0] : f[1], 1);
  const float lo = b0 ? r : mine, hi = b0 ? mine : r;
  const float lo2 = __shfl_xor_sync(~0u, lo, 2), hi2 = __shfl_xor_sync(~0u, hi, 2);
  o[0] = b1 ? lo2 : lo; o[1] = b1 ? hi2 : hi; o[2] = b1 ? lo : lo2; o[3] = b1 ? hi : hi2;
}
__device__ __forceinline__ void quad_scatter(const float* s, int q, float* f) {
  const bool b0 = q & 1, b1 = q & 2;
  const float lo = b1 ? s[2] : s[0], hi = b1 ? s[3] : s[1];
  const float mine = b0 ? hi : lo;
  const float r = __shfl_xor_sync(~0u, b0 ? lo : hi, 1);
  f[0] = b0 ? r : mine; f[1] = b0 ? mine : r;
}

__device__ __forceinline__ void b_consumer(const Params& P, int bi, int tb, int g, int wg, long long t_start) {
  const int tid = threadIdx.x & 127, w = tid >> 5, lane = tid & 31, gi = lane >> 2, q = lane & 3;
  const bool last = tb == 12;

  if (threadIdx.x < 168) sts128(B_ZERO + threadIdx.x * 16, 0u, 0u, 0u, 0u);
  prep_fold(B_STG, BAR_P, BAR_KV0, t_start);
  mbar_arrive1(BAR_PREP);
  if (wg) {
    mbar_arrive1(BAR_TOK);
    const int p = 128 * g + tid;
    const float are = ldbf(P.lre + p), aim = ldbf(P.lim + p), ldt = ldbf(P.logdt + p);
    const float dt = __bfloat162float(__float2bfloat16_rn(expf(ldt)));
    const float mag = expf(dt * are);
    float sn, cs;
    sincospif(dt * aim * 0.3183098861837907f, &sn, &cs);
    const float lr = mag * cs, li = mag * sn;
    const float inv = 2.0f * rcp(fmaf(are, are, aim * aim));
    float mr, mi, nr, ni;
    cmul(lr, li, lr, li, nr, ni);
    cmul(nr, ni, nr, ni, nr, ni);
    cmul(nr, ni, nr, ni, nr, ni);
    cmul(nr, ni, nr, ni, mr, mi);
    cmul(mr, mi, mr, mi, mr, mi);
    if (!last) cmul(mr, mi, nr, ni, mr, mi);
    sts128(B_CONST + tid * 16, __float_as_uint(lr), __float_as_uint(li), __float_as_uint(fmaf(lr - 1.0f, are, li * aim) * inv),
           __float_as_uint(fmaf(li, are, (1.0f - lr) * aim) * inv));
    asm volatile("st.shared.v2.f32 [%0], {%1,%2};" ::"r"(B_CONST + 2048 + tid * 8), "f"(mr), "f"(mi) : "memory");
    asm volatile("st.shared.u32 [%0], %1;" ::"r"(B_CONST + 3072), "r"((load_epoch_raw(P) + 1) & 3) : "memory");
    mbar_arrive1(BAR_V);
    if (bi < 40) {
      mbar_wait(BAR_P1, 0);
      prep_wo(B_STG);
      mbar_arrive1(BAR_FREE);
    }
  }

  float u[80], v[80];
  reg_kill<80>(u);
  reg_kill<80>(v);
#pragma unroll 1
  for (int it = 0;; it++) {
    const int task = uniform(it);
    if (task < 2) mbar_wait(BAR_TOK + 8 * wg, task);
    TS((task ? 7 + 2 * task : 1) + 16 * wg);
    b_mainloop(u, v, task == 2, task, task + wg == 1, BAR_RED + 8 * (wg ^ 1), BAR_O + 8 * (wg ^ 1));
    if (!B_HOLD && task == 0) mbar_arrive1(BAR_TOK + 8 * (wg ^ 1));
    wg_wait<0>();
    reg_fence<80>(u);
    reg_fence<80>(v);
    mbar_arrive1(BAR_EMPTY + 32);
    TS((task ? 8 + 2 * task : 2) + 16 * wg);
    if (task == 1) continue;
    if (task == 2) break;

    const int pl = 64 * wg + 16 * w + gi, p = 128 * g + pl + 8 * (q & 1);
    uint32_t tag, k0[4], k1[4];
    float mr, mi;
    mbar_wait(BAR_V, 0);
    asm volatile("ld.shared.u32 %0, [%1];" : "=r"(tag) : "r"(B_CONST + 3072) : "memory");
    lds128(B_CONST + pl * 16, k0);
    lds128(B_CONST + pl * 16 + 128, k1);
    asm volatile("ld.shared.v2.f32 {%0,%1}, [%2];" : "=f"(mr), "=f"(mi) : "r"(B_CONST + 2048 + (pl + 8 * (q & 1)) * 8) : "memory");
    const float Lr[2] = {__uint_as_float(k0[0]), __uint_as_float(k1[0])}, Li[2] = {__uint_as_float(k0[1]), __uint_as_float(k1[1])};
    const float Cr[2] = {__uint_as_float(k0[2]), __uint_as_float(k1[2])}, Ci[2] = {__uint_as_float(k0[3]), __uint_as_float(k1[3])};
    float hr[2] = {0.f, 0.f}, hi[2] = {0.f, 0.f};
#pragma unroll
    for (int t = 0; t < 40; t++)
#pragma unroll
      for (int a = 0; a < 2; a++) {
        const int r = 4 * (t >> 1) + 2 * a + (t & 1);
        cstep(Lr[a], Li[a], hr[a], hi[a], u[r], v[r]);
      }
    if (B_HOLD == 1) mbar_arrive1(BAR_TOK + 8 * (wg ^ 1) + (__float_as_uint(hr[0]) == 0x7fc12345u));
    float fr[4], fi[4];
    quad_gather(hr, q, fr);
    quad_gather(hi, q, fi);
    float sr = fr[0], si = fi[0];
#pragma unroll
    for (int a = 1; a < 4; a++) cstep(mr, mi, sr, si, fr[a], fi[a]);
    unsigned long long* fin = P.s->fin + tb * 640 + p;
    if (q < 2)
      asm volatile("st.relaxed.gpu.global.v2.b32 [%0], {%1, %2};" ::"l"(fin), "r"((__float_as_uint(sr) & ~3u) | tag), "r"((__float_as_uint(si) & ~3u) | tag) : "memory");
    if (B_HOLD == 2) mbar_arrive1(BAR_TOK + 8 * (wg ^ 1));
    TS(3 + 16 * wg);
    reg_fence<80>(u);
    reg_fence<80>(v);
#pragma unroll
    for (int a = 0; a < 2; a++) {
      const float kr = Cr[a], ki = Ci[a];
#pragma unroll
      for (int t = 0; t < 40; t++) {
        const int r = 4 * (t >> 1) + 2 * a + (t & 1);
        const float xr = u[r], xi = v[r];
        u[r] = fmaf(kr, xr, -ki * xi);
        v[r] = fmaf(-kr, xi, -ki * xr);
      }
    }
    reg_fence<80>(u);
    reg_fence<80>(v);
    if (B_HOLD == 3) mbar_arrive1(BAR_TOK + 8 * (wg ^ 1) + (__float_as_uint(u[79]) == 0x7fc12345u));
    float nr, ni, fr6, fi6;
    cmul(mr, mi, mr, mi, nr, ni);
    cmul(nr, ni, nr, ni, nr, ni);
    if (last) cmul(nr, ni, mr, mi, nr, ni);
    cmul(nr, ni, nr, ni, fr6, fi6);
    cmul(fr6, fi6, nr, ni, fr6, fi6);
    cmul(fr6, fi6, fr6, fi6, fr6, fi6);
    if (q & 2) { fr6 = 1.f; fi6 = 0.f; }
    uint32_t er[6], ei[6];
#pragma unroll
    for (int k = 0; k < 6; k++) er[k] = ei[k] = tag;
    const int back = (q & 2) ? 6 : 12;
    fin -= back * 640;
    uint32_t bad;
    do {
      bad = 0;
#pragma unroll
      for (int k = 0; k < 6; k++)
        asm volatile("{ .reg .pred p; setp.le.s32 p, %3, %4;\n@p ld.relaxed.gpu.global.v2.b32 {%0, %1}, [%2]; }"
                     : "+r"(er[k]), "+r"(ei[k]) : "l"(fin + k * 640), "r"(back - tb), "r"(k) : "memory");
#pragma unroll
      for (int k = 0; k < 6; k++) bad |= (er[k] ^ tag) | (ei[k] ^ tag);
    } while (__any_sync(~0u, bad & 3));
    sr = 0.f; si = 0.f;
#pragma unroll
    for (int k = 0; k < 6; k++) cstep(nr, ni, sr, si, __uint_as_float(er[k] ^ tag), __uint_as_float(ei[k] ^ tag));
    cmul(fr6, fi6, sr, si, sr, si);
    sr += __shfl_xor_sync(~0u, sr, 2);
    si += __shfl_xor_sync(~0u, si, 2);
    TS(4 + 16 * wg);
#pragma unroll
    for (int a = 0; a < 4; a++) {
      const float xr = sr, xi = si;
      cstep(mr, mi, sr, si, fr[a], fi[a]);
      fr[a] = xr; fi[a] = xi;
    }
    quad_scatter(fr, q, hr);
    quad_scatter(fi, q, hi);
#pragma unroll
    for (int a = 0; a < 2; a++) {
      const float xr = hr[a], xi = hi[a];
      hr[a] = fmaf(Cr[a], xr, -Ci[a] * xi);
      hi[a] = fmaf(-Cr[a], xi, -Ci[a] * xr);
    }
    if (last) {
#pragma unroll
      for (int a = 0; a < 2; a++) {
        u[13 + 2 * a] = hr[a]; v[13 + 2 * a] = hi[a];
        hr[a] = 0.f; hi[a] = 0.f;
      }
    }
    const uint32_t ha = B_STG + (lane >> 4) * kBlob + (lane & 7) * 128 + (((2 * w + ((lane >> 3) & 1)) ^ (lane & 7)) << 4);
    mbar_wait(wg ? BAR_STG : BAR_KVR, 0);
    TS(5 + 16 * wg);
    mbar_wait(BAR_RED + 8 * wg, 0);
    TS(6 + 16 * wg);
#pragma unroll
    for (int j = 0; j < 20; j++) {
      uint32_t kr[2], ki[2];
#pragma unroll
      for (int a = 0; a < 2; a++) {
        const int r = 4 * j + 2 * a;
        cstep(Lr[a], -Li[a], hr[a], hi[a], u[r], v[r]);
        const float xr = hr[a], xi = hi[a];
        cstep(Lr[a], -Li[a], hr[a], hi[a], u[r + 1], v[r + 1]);
        kr[a] = pack2(xr, hr[a]);
        ki[a] = pack2(xi, hi[a]);
      }
      stsm4t(ha + j * 1024, kr[0], kr[1], ki[0], ki[1]);
    }
    fence_async_smem();
    mbar_arrive1(BAR_O + 8 * wg);
    TS(8 + 16 * wg);
    if (wg) return;
  }

  const int dl = 32 * w + 4 * gi;
  const uint2 dk = __ldg(reinterpret_cast<const uint2*>(P.dskip + 128 * g + dl));
  const float k0 = bf_lo(dk.x), k1 = bf_hi(dk.x), k2 = bf_lo(dk.y), k3 = bf_hi(dk.y);
  float* o = P.out + (size_t)(last ? 1920 + 32 * q - 8 : 160 * tb + 40 * q) * 1280 + 640 + 128 * g + dl;
  const uint32_t xa = B_STG + (w >> 1) * kBlob + q * 256 + (gi & 1) * 8;
  const uint32_t xc = (4 * (w & 1) + (gi >> 1)) ^ (2 * q);
  mbar_wait(BAR_W, 0);
#pragma unroll
  for (int t = 0; t < 40; t++) {
    const int r = 4 * (t >> 1) + (t & 1);
    uint32_t x0, x1;
    asm volatile("ld.shared.v2.b32 {%0,%1}, [%2];" : "=r"(x0), "=r"(x1) : "r"(xa + (t >> 1) * 1024 + (t & 1) * 128 + ((xc ^ (t & 1)) << 4)));
    asm volatile("{ .reg .pred p; setp.ne.s32 p, %5, 0;\n@p st.global.v4.f32 [%0], {%1, %2, %3, %4}; }" ::"l"(o + t * 1280),
                 "f"(fmaf(bf_lo(x0), k0, u[r])), "f"(fmaf(bf_hi(x0), k1, u[r + 2])), "f"(fmaf(bf_lo(x1), k2, v[r])), "f"(fmaf(bf_hi(x1), k3, v[r + 2])),
                 "r"((int)(t >= 8 || !last)));
  }
  TS(15);
}

__global__ void __launch_bounds__(kThreads, 1) fused_kernel(const __grid_constant__ Params P) {
  extern __shared__ __align__(1024) unsigned char smem[];
  const long long t_start = 0;
  const int b = blockIdx.x;
  const bool isA = b < 128 && (b & 2), isB = !isA && b <= 128;
  const int idx = b < 128 ? (b >> 2) * 2 + (b & 1) : b - 64;
  const int warp = uniform(threadIdx.x >> 5), wg = warp >> 2;
  if (warp == 8 || warp == 9) {
    if (threadIdx.x == 256) {
#pragma unroll
      for (int i = 0; i < 6; i++) { mbar_init(BAR_FULL + 8 * i, isB ? 2 : 1); mbar_init(BAR_EMPTY + 8 * i, isB ? 4 : 8); }
#pragma unroll
      for (int i = 0; i < 10; i++) mbar_init(BAR_X + 8 * i, 1);
    }
    if (threadIdx.x == 288) {
#pragma unroll
      for (uint32_t a = BAR_TOK; a <= BAR_STG1; a += 8)
        if (a < BAR_X || a >= BAR_FREE) mbar_init(a, a == BAR_V ? (isA ? 8 : 4) : a == BAR_PREP ? (isA ? 1 : 8) : bar_count(a));
    }
    asm volatile("fence.mbarrier_init.release.cluster;" ::: "memory");
    __syncwarp();
    asm volatile("bar.arrive 0, 384;" ::: "memory");
    if (warp == 9 && isB) fold_load(P, idx, B_STG, BAR_P, BAR_KV0);
    if (warp == 8 && isA) {
      mbar_expect(BAR_X, 8192);
      tma2d(A_X, &P.xa, 0, (idx & 31) * 64, BAR_X);
      mbar_expect(BAR_FULL, kBlob);
      tma3d(A_RING, &P.wv, 0, 0, 20 + 5 * (idx >> 5), BAR_FULL);
      TS1(38);
    }
  } else {
    asm volatile("bar.sync 0, 384;" ::: "memory");
  }
  const int rb = idx & 31, half = idx >> 5;
  const int tb = idx / 5, g = idx % 5;
  if (wg == 2) {
    asm volatile("setmaxnreg.dec.sync.aligned.u32 40;");
    if (warp == 8) {
      TS1(37);
      if (isA) a_producer(P, rb, half, t_start);
      else if (isB) b_producer_w(P, g, t_start);
      else {
#pragma unroll 1
        for (int n = 0, c0 = clock(); n < 5; n++) {
          pace(c0, P_PACE0 + n * P_PACE);
          fold_load(P, idx + 3 * n, B_RING + n * 32768, BAR_FULL + 8 * n, BAR_X + 8 * n);
        }
#pragma unroll 1
        for (int n = 0; n < 5; n++) {
          mbar_wait(BAR_EMPTY + 8 * n, 0);
          bulk_store(P.s->w + (size_t)(idx + 3 * n) * kBlob, B_RING + n * 32768, kBlob);
        }
        bulk_wait();
        if (threadIdx.x < 261) asm volatile("red.release.gpu.global.add.u32 [%0], 1;" ::"l"(P.s->cnt + (C_W + (idx + 3 * (threadIdx.x - 256)) / 10) * 32) : "memory");
        __syncwarp();
        TS1(34);
      }
    } else if (warp == 9) {
      if (isA) a_helper(P, rb, half, t_start);
      else if (isB) b_helper(P, idx, tb, g, t_start);
    } else if (warp == 10) {
      if (isA) {
        const unsigned ep = load_epoch(P);
        a_poller(P, half, ep);
        a_exchange(P, rb, half, ep, t_start);
      } else if (isB) {
        b_producer_x(P, tb, g, t_start);
      }
    } else {
      if ((uint32_t)__cvta_generic_to_shared(smem) != SB) __trap();
      const unsigned ep = load_epoch(P);
      const long long t0 = clock64();
      uint32_t ok;
      do {
        asm volatile("{ .reg .pred p; mbarrier.try_wait.parity.shared::cta.b64 p, [%1], 0, 100000; selp.u32 %0, 1, 0, p; }" : "=r"(ok) : "r"(BAR_DONE) : "memory");
        if (clock64() - t0 > 4000000000ll) __trap();
      } while (!ok);
      P.s->ep[b * 32] = ep;
    }
    if (warp < 11) mbar_arrive1(BAR_DONE);
  } else {
    asm volatile("setmaxnreg.inc.sync.aligned.u32 232;");
    if (wg && isA) mbar_arrive1(BAR_TOK);
    if (isA) {
      a_consumer(P, rb, half, wg, t_start);
    } else if (isB) {
      b_consumer(P, idx, tb, g, wg, t_start);
    } else {
#pragma unroll 1
      for (int n = 0; n < 5; n++) {
        prep_fold(B_RING + n * 32768, BAR_FULL + 8 * n, BAR_X + 8 * n, t_start);
        mbar_arrive1(BAR_EMPTY + 8 * n);
      }
      TS(35);
    }
    mbar_arrive1(BAR_DONE);
  }
}

typedef CUresult (*EncodeFn)(CUtensorMap*, CUtensorMapDataType, cuuint32_t, void*, const cuuint64_t*, const cuuint64_t*,
                             const cuuint32_t*, const cuuint32_t*, CUtensorMapInterleave, CUtensorMapSwizzle,
                             CUtensorMapL2promotion, CUtensorMapFloatOOBfill);

void encode(EncodeFn fn, CUtensorMap* m, const void* ptr, int rank, const cuuint64_t* dims, const cuuint64_t* strides, const cuuint32_t* box) {
  const cuuint32_t es[5] = {1, 1, 1, 1, 1};
  fn(m, CU_TENSOR_MAP_DATA_TYPE_BFLOAT16, rank, const_cast<void*>(ptr), dims, strides, box, es, CU_TENSOR_MAP_INTERLEAVE_NONE,
     CU_TENSOR_MAP_SWIZZLE_128B, CU_TENSOR_MAP_L2_PROMOTION_L2_128B, CU_TENSOR_MAP_FLOAT_OOB_FILL_NONE);
}

}

extern "C" void kernel_launch(void* const* d_in, const int* in_sizes, int n_in, void* d_out, int out_size) {
  (void)in_sizes; (void)n_in; (void)out_size;
  void* fp = nullptr;
  cudaDriverEntryPointQueryResult qr;
  cudaGetDriverEntryPoint("cuTensorMapEncodeTiled", &fp, cudaEnableDefault, &qr);
  EncodeFn fn = (EncodeFn)fp;
  const __nv_bfloat16* const* in = (const __nv_bfloat16* const*)d_in;
  Params P;
  constexpr cuuint64_t R = kD * 2;
  {
    const cuuint64_t d[2] = {kD, kSeq}, s[1] = {R};
    const cuuint32_t b[2] = {64, 64};
    encode(fn, &P.xa, in[0], 2, d, s, b);
  }
  {
    const cuuint64_t d[3] = {64, kD, 30}, s[2] = {3 * R, 128};
    const cuuint32_t b[3] = {64, 32, 5};
    encode(fn, &P.wv, in[1], 3, d, s, b);
  }
  {
    const cuuint64_t d[5] = {kD, 2, 4, 20, 12}, s[4] = {R, 40 * R, 2 * R, 160 * R};
    const cuuint32_t b[5] = {64, 2, 4, 20, 1};
    encode(fn, &P.xb, in[4], 5, d, s, b);
    const cuuint64_t dl[5] = {kD, 2, 4, 16, 1}, sl[4] = {R, 32 * R, 2 * R, 160 * R};
    encode(fn, &P.xbl, in[4] + 1920 * kD, 5, dl, sl, b);
  }
  {
    const cuuint64_t d[2] = {kD, kD}, s[1] = {R};
    const cuuint32_t b[2] = {64, 64};
    encode(fn, &P.bre, in[7], 2, d, s, b);
    encode(fn, &P.bim, in[8], 2, d, s, b);
  }
  {
    const cuuint64_t d[5] = {kD, 8, 2, 20, 2}, s[4] = {4 * R, R, 32 * R, 2 * R};
    const cuuint32_t b[5] = {64, 8, 2, 4, 2};
    encode(fn, &P.cre, in[9], 5, d, s, b);
    encode(fn, &P.cim, in[10], 5, d, s, b);
  }
  {
    const cuuint64_t d[5] = {3 * kD, 2, 4, 4, 20}, s[4] = {3 * R, 24 * R, 6 * R, 96 * R};
    const cuuint32_t b[5] = {64, 2, 4, 4, 1}, b2[5] = {64, 2, 4, 4, 2};
    encode(fn, &P.wp, in[1], 5, d, s, b2);
    const cuuint64_t d2[5] = {kD, 2, 4, 4, 20}, s2[4] = {R, 8 * R, 2 * R, 32 * R};
    encode(fn, &P.wop, in[3], 5, d2, s2, b);
  }
  P.wphi = in[2]; P.cre_p = in[9]; P.cim_p = in[10];
  P.lre = in[5]; P.lim = in[6]; P.logdt = in[11]; P.dskip = in[12];
  P.out = (float*)d_out;
  P.one = 1;
  cudaGetSymbolAddress((void**)&P.s, g_scratch);
  cudaFuncSetAttribute(fused_kernel, cudaFuncAttributeMaxDynamicSharedMemorySize, kSmem);
  fused_kernel<<<kGrid, kThreads, kSmem>>>(P);
}
```

```cpp
#define KV_R 2
#define B_PS 0
#include <cuda_runtime.h>
#include <cuda_bf16.h>
#include <cuda.h>
#include <stdint.h>

namespace {

constexpr int kSeq = 2048;
constexpr int kD = 640;
constexpr int kGrid = 132;
constexpr int kThreads = 384;

constexpr uint32_t kBlob = 20480;
constexpr uint32_t kFold = 19456;
constexpr uint32_t kPair = 5152;
constexpr uint32_t kHalf = 20576;
constexpr uint32_t kKvBytes = 16384;
constexpr int A_NS = 5;

constexpr uint32_t SB = 1024;
constexpr uint32_t BARS = SB;
constexpr uint32_t A_ONES = SB + 640;
constexpr uint32_t A_PHI = SB + 6976;
constexpr uint32_t A_X = A_PHI + 2 * kHalf;
constexpr uint32_t A_RING = A_X + 81920;
constexpr uint32_t B_RING = SB + 1024;
constexpr uint32_t B_SLOT = 36864;
constexpr uint32_t B_STG = B_RING + 5 * B_SLOT;
constexpr uint32_t B_ZERO = B_STG + 40960;
constexpr uint32_t B_CONST = B_ZERO + 2048;
constexpr uint32_t kSmem = 232448;

constexpr uint32_t BAR_FULL = BARS, BAR_EMPTY = BARS + 48, BAR_TOK = BARS + 96, BAR_STG = BARS + 112, BAR_V = BARS + 120,
                   BAR_O = BARS + 128, BAR_KV0 = BARS + 144, BAR_P = BARS + 152, BAR_KVR = BARS + 160, BAR_P1 = BARS + 176,
                   BAR_X = BARS + 184, BAR_FREE = BARS + 264, BAR_RED = BARS + 280, BAR_DONE = BARS + 296, BAR_W = BARS + 304,
                   BAR_DUMMY = BARS + 328, BAR_PREP = BARS + 336, BAR_QD = BARS + 344, BAR_QF = BARS + 352,
                   BAR_STG1 = BARS + 360, BAR_QS = BARS + 368, BAR_QF1 = BARS + 400, BAR_WA = BARS + 408, BAR_PA = BARS + 448;
__host__ __device__ constexpr uint32_t bar_count(uint32_t a) {
  return a == BAR_DONE ? 11 : (a == BAR_PREP || a == BAR_PA) ? 8 : a == BAR_PA + 8 ? 4 : a == BAR_DUMMY ? 1024
       : (a == BAR_TOK || a == BAR_TOK + 8 || a == BAR_V || a == BAR_O || a == BAR_O + 8 || (a >= BAR_FREE && a < BAR_DONE) || a == BAR_QD || a == BAR_QF || (a >= BAR_QS && a <= BAR_QF1)) ? 4 : 1;
}
constexpr uint32_t kPrepW = 24576, kPrepPhi = 6400;
enum { C_W = 0, C_KV = 2 * 32, C_H = 6 * 32, C_O = 32 * 32 };

struct Scratch {
  unsigned char kv[4 * KV_R * kKvBytes];
  unsigned long long fin[13 * 640];
  unsigned cnt[176 * 32];
  unsigned ep[136 * 32];
  unsigned char w[3 * 4 * 10 * kBlob];
  unsigned char ox[32 * 4 * kBlob];
  unsigned char h[13 * 20 * kBlob];
};
__device__ __align__(1024) Scratch g_scratch;

struct Params {
  Scratch* s;
  float* out;
  const __nv_bfloat16 *wphi, *cre_p, *cim_p, *lre, *lim, *logdt, *dskip;
  int one;
  CUtensorMap xa, wv, wp, xb, bre, bim, xbl, cre, cim, wop;
};

#define TS(slot)
#define TS1(slot)
#define ST(i)

template <int TB>
__device__ __forceinline__ void wgmma_n128(float* d, uint64_t da, uint64_t db, int sc) {
  asm volatile("{ .reg .pred p; setp.ne.b32 p, %66, 0;\n"
    "wgmma.mma_async.sync.aligned.m64n128k16.f32.bf16.bf16 {%0,%1,%2,%3,%4,%5,%6,%7,%8,%9,%10,%11,%12,%13,%14,%15,%16,%17,%18,%19,%20,%21,%22,%23,%24,%25,%26,%27,%28,%29,%30,%31,%32,%33,%34,%35,%36,%37,%38,%39,%40,%41,%42,%43,%44,%45,%46,%47,%48,%49,%50,%51,%52,%53,%54,%55,%56,%57,%58,%59,%60,%61,%62,%63}, %64, %65, p, 1, 1, 0, %67; }"
    : "+f"(d[0]),"+f"(d[1]),"+f"(d[2]),"+f"(d[3]),"+f"(d[4]),"+f"(d[5]),"+f"(d[6]),"+f"(d[7]),"+f"(d[8]),"+f"(d[9]),"+f"(d[10]),"+f"(d[11]),"+f"(d[12]),"+f"(d[13]),"+f"(d[14]),"+f"(d[15]),"+f"(d[16]),"+f"(d[17]),"+f"(d[18]),"+f"(d[19]),"+f"(d[20]),"+f"(d[21]),"+f"(d[22]),"+f"(d[23]),"+f"(d[24]),"+f"(d[25]),"+f"(d[26]),"+f"(d[27]),"+f"(d[28]),"+f"(d[29]),"+f"(d[30]),"+f"(d[31]),"+f"(d[32]),"+f"(d[33]),"+f"(d[34]),"+f"(d[35]),"+f"(d[36]),"+f"(d[37]),"+f"(d[38]),"+f"(d[39]),"+f"(d[40]),"+f"(d[41]),"+f"(d[42]),"+f"(d[43]),"+f"(d[44]),"+f"(d[45]),"+f"(d[46]),"+f"(d[47]),"+f"(d[48]),"+f"(d[49]),"+f"(d[50]),"+f"(d[51]),"+f"(d[52]),"+f"(d[53]),"+f"(d[54]),"+f"(d[55]),"+f"(d[56]),"+f"(d[57]),"+f"(d[58]),"+f"(d[59]),"+f"(d[60]),"+f"(d[61]),"+f"(d[62]),"+f"(d[63])
    : "l"(da), "l"(db), "r"(sc), "n"(TB));
}
template <int TB>
__device__ __forceinline__ void wgmma_n192(float* d, uint64_t da, uint64_t db, int sc) {
  asm volatile("{ .reg .pred p; setp.ne.b32 p, %98, 0;\n"
    "wgmma.mma_async.sync.aligned.m64n192k16.f32.bf16.bf16 {%0,%1,%2,%3,%4,%5,%6,%7,%8,%9,%10,%11,%12,%13,%14,%15,%16,%17,%18,%19,%20,%21,%22,%23,%24,%25,%26,%27,%28,%29,%30,%31,%32,%33,%34,%35,%36,%37,%38,%39,%40,%41,%42,%43,%44,%45,%46,%47,%48,%49,%50,%51,%52,%53,%54,%55,%56,%57,%58,%59,%60,%61,%62,%63,%64,%65,%66,%67,%68,%69,%70,%71,%72,%73,%74,%75,%76,%77,%78,%79,%80,%81,%82,%83,%84,%85,%86,%87,%88,%89,%90,%91,%92,%93,%94,%95}, %96, %97, p, 1, 1, 0, %99; }"
    : "+f"(d[0]),"+f"(d[1]),"+f"(d[2]),"+f"(d[3]),"+f"(d[4]),"+f"(d[5]),"+f"(d[6]),"+f"(d[7]),"+f"(d[8]),"+f"(d[9]),"+f"(d[10]),"+f"(d[11]),"+f"(d[12]),"+f"(d[13]),"+f"(d[14]),"+f"(d[15]),"+f"(d[16]),"+f"(d[17]),"+f"(d[18]),"+f"(d[19]),"+f"(d[20]),"+f"(d[21]),"+f"(d[22]),"+f"(d[23]),"+f"(d[24]),"+f"(d[25]),"+f"(d[26]),"+f"(d[27]),"+f"(d[28]),"+f"(d[29]),"+f"(d[30]),"+f"(d[31]),"+f"(d[32]),"+f"(d[33]),"+f"(d[34]),"+f"(d[35]),"+f"(d[36]),"+f"(d[37]),"+f"(d[38]),"+f"(d[39]),"+f"(d[40]),"+f"(d[41]),"+f"(d[42]),"+f"(d[43]),"+f"(d[44]),"+f"(d[45]),"+f"(d[46]),"+f"(d[47]),"+f"(d[48]),"+f"(d[49]),"+f"(d[50]),"+f"(d[51]),"+f"(d[52]),"+f"(d[53]),"+f"(d[54]),"+f"(d[55]),"+f"(d[56]),"+f"(d[57]),"+f"(d[58]),"+f"(d[59]),"+f"(d[60]),"+f"(d[61]),"+f"(d[62]),"+f"(d[63]),"+f"(d[64]),"+f"(d[65]),"+f"(d[66]),"+f"(d[67]),"+f"(d[68]),"+f"(d[69]),"+f"(d[70]),"+f"(d[71]),"+f"(d[72]),"+f"(d[73]),"+f"(d[74]),"+f"(d[75]),"+f"(d[76]),"+f"(d[77]),"+f"(d[78]),"+f"(d[79]),"+f"(d[80]),"+f"(d[81]),"+f"(d[82]),"+f"(d[83]),"+f"(d[84]),"+f"(d[85]),"+f"(d[86]),"+f"(d[87]),"+f"(d[88]),"+f"(d[89]),"+f"(d[90]),"+f"(d[91]),"+f"(d[92]),"+f"(d[93]),"+f"(d[94]),"+f"(d[95])
    : "l"(da), "l"(db), "r"(sc), "n"(TB));
}

__device__ __forceinline__ void wg_fence() { asm volatile("wgmma.fence.sync.aligned;" ::: "memory"); }
__device__ __forceinline__ void wg_commit() { asm volatile("wgmma.commit_group.sync.aligned;" ::: "memory"); }
template <int N> __device__ __forceinline__ void wg_wait() { asm volatile("wgmma.wait_group.sync.aligned %0;" ::"n"(N) : "memory"); }
template <int N> __device__ __forceinline__ void reg_fence(float* d) {
#pragma unroll
  for (int i = 0; i < N; i++) asm volatile("" : "+f"(d[i])::"memory");
}
template <int N> __device__ __forceinline__ void reg_kill(float* d) {
#pragma unroll
  for (int i = 0; i < N; i++) asm volatile("" : "=f"(d[i]));
}
__host__ __device__ constexpr uint32_t desc_lo(uint32_t addr, uint32_t lbo) { return (addr >> 4) | ((lbo >> 4) << 16); }
constexpr uint32_t kHiSw128 = (1024 >> 4) | (1u << 30);
constexpr uint32_t kHiPlain = 128 >> 4;
__device__ __forceinline__ uint64_t mkdesc(uint32_t lo, uint32_t hi) { return ((uint64_t)hi << 32) | lo; }
__device__ __forceinline__ int uniform(int v) { return __shfl_sync(~0u, v, 0); }

__device__ __forceinline__ void a_mainloop152(float* d, uint32_t tok) {
  asm volatile(
    "{ .reg .pred pe, pw, pz, pt; .reg .b32 hb, t, u; .reg .b64 dA, dB;\n"
    "mov.b32 hb, %80; mov.u32 t, %%laneid; setp.lt.u32 pe, t, 2; setp.ne.b32 pz, 0, 0; setp.eq.b32 pt, 0, 0;\n"
    "mov.b32 t, %78+0;\n"
    "W0: mbarrier.try_wait.parity.shared::cta.b64 pw, [t], 0, 100000;\n"
    "@!pw bra W0;\n"
    "wgmma.fence.sync.aligned;\n"
    "mov.b32 t, %76+0; mov.b32 u, %77+0;\n"
    "mov.b64 dA, {t, hb}; mov.b64 dB, {u, hb};\n"
    "wgmma.mma_async.sync.aligned.m64n152k16.f32.bf16.bf16 {%0,%1,%2,%3,%4,%5,%6,%7,%8,%9,%10,%11,%12,%13,%14,%15,%16,%17,%18,%19,%20,%21,%22,%23,%24,%25,%26,%27,%28,%29,%30,%31,%32,%33,%34,%35,%36,%37,%38,%39,%40,%41,%42,%43,%44,%45,%46,%47,%48,%49,%50,%51,%52,%53,%54,%55,%56,%57,%58,%59,%60,%61,%62,%63,%64,%65,%66,%67,%68,%69,%70,%71,%72,%73,%74,%75}, dA, dB, pz, 1, 1, 0, 0;\n"
    "mov.b32 t, %76+2; mov.b32 u, %77+2;\n"
    "mov.b64 dA, {t, hb}; mov.b64 dB, {u, hb};\n"
    "wgmma.mma_async.sync.aligned.m64n152k16.f32.bf16.bf16 {%0,%1,%2,%3,%4,%5,%6,%7,%8,%9,%10,%11,%12,%13,%14,%15,%16,%17,%18,%19,%20,%21,%22,%23,%24,%25,%26,%27,%28,%29,%30,%31,%32,%33,%34,%35,%36,%37,%38,%39,%40,%41,%42,%43,%44,%45,%46,%47,%48,%49,%50,%51,%52,%53,%54,%55,%56,%57,%58,%59,%60,%61,%62,%63,%64,%65,%66,%67,%68,%69,%70,%71,%72,%73,%74,%75}, dA, dB, pt, 1, 1, 0, 0;\n"
    "mov.b32 t, %76+4; mov.b32 u, %77+4;\n"
    "mov.b64 dA, {t, hb}; mov.b64 dB, {u, hb};\n"
    "wgmma.mma_async.sync.aligned.m64n152k16.f32.bf16.bf16 {%0,%1,%2,%3,%4,%5,%6,%7,%8,%9,%10,%11,%12,%13,%14,%15,%16,%17,%18,%19,%20,%21,%22,%23,%24,%25,%26,%27,%28,%29,%30,%31,%32,%33,%34,%35,%36,%37,%38,%39,%40,%41,%42,%43,%44,%45,%46,%47,%48,%49,%50,%51,%52,%53,%54,%55,%56,%57,%58,%59,%60,%61,%62,%63,%64,%65,%66,%67,%68,%69,%70,%71,%72,%73,%74,%75}, dA, dB, pt, 1, 1, 0, 0;\n"
    "mov.b32 t, %76+6; mov.b32 u, %77+6;\n"
    "mov.b64 dA, {t, hb}; mov.b64 dB, {u, hb};\n"
    "wgmma.mma_async.sync.aligned.m64n152k16.f32.bf16.bf16 {%0,%1,%2,%3,%4,%5,%6,%7,%8,%9,%10,%11,%12,%13,%14,%15,%16,%17,%18,%19,%20,%21,%22,%23,%24,%25,%26,%27,%28,%29,%30,%31,%32,%33,%34,%35,%36,%37,%38,%39,%40,%41,%42,%43,%44,%45,%46,%47,%48,%49,%50,%51,%52,%53,%54,%55,%56,%57,%58,%59,%60,%61,%62,%63,%64,%65,%66,%67,%68,%69,%70,%71,%72,%73,%74,%75}, dA, dB, pt, 1, 1, 0, 0;\n"
    "wgmma.commit_group.sync.aligned;\n"
    "mov.b32 t, %78+8;\n"
    "W1: mbarrier.try_wait.parity.shared::cta.b64 pw, [t], 0, 100000;\n"
    "@!pw bra W1;\n"
    "wgmma.fence.sync.aligned;\n"
    "mov.b32 t, %76+512; mov.b32 u, %77+1280;\n"
    "mov.b64 dA, {t, hb}; mov.b64 dB, {u, hb};\n"
    "wgmma.mma_async.sync.aligned.m64n152k16.f32.bf16.bf16 {%0,%1,%2,%3,%4,%5,%6,%7,%8,%9,%10,%11,%12,%13,%14,%15,%16,%17,%18,%19,%20,%21,%22,%23,%24,%25,%26,%27,%28,%29,%30,%31,%32,%33,%34,%35,%36,%37,%38,%39,%40,%41,%42,%43,%44,%45,%46,%47,%48,%49,%50,%51,%52,%53,%54,%55,%56,%57,%58,%59,%60,%61,%62,%63,%64,%65,%66,%67,%68,%69,%70,%71,%72,%73,%74,%75}, dA, dB, pt, 1, 1, 0, 0;\n"
    "mov.b32 t, %76+514; mov.b32 u, %77+1282;\n"
    "mov.b64 dA, {t, hb}; mov.b64 dB, {u, hb};\n"
    "wgmma.mma_async.sync.aligned.m64n152k16.f32.bf16.bf16 {%0,%1,%2,%3,%4,%5,%6,%7,%8,%9,%10,%11,%12,%13,%14,%15,%16,%17,%18,%19,%20,%21,%22,%23,%24,%25,%26,%27,%28,%29,%30,%31,%32,%33,%34,%35,%36,%37,%38,%39,%40,%41,%42,%43,%44,%45,%46,%47,%48,%49,%50,%51,%52,%53,%54,%55,%56,%57,%58,%59,%60,%61,%62,%63,%64,%65,%66,%67,%68,%69,%70,%71,%72,%73,%74,%75}, dA, dB, pt, 1, 1, 0, 0;\n"
    "wgmma.commit_group.sync.aligned;\n"
    "wgmma.wait_group.sync.aligned 1;\n"
    "mov.b32 t, %79+0;\n"
    "@pe mbarrier.arrive.shared::cta.b64 _, [t];\n"
    "mov.b32 t, %76+516; mov.b32 u, %77+1284;\n"
    "mov.b64 dA, {t, hb}; mov.b64 dB, {u, hb};\n"
    "wgmma.mma_async.sync.aligned.m64n152k16.f32.bf16.bf16 {%0,%1,%2,%3,%4,%5,%6,%7,%8,%9,%10,%11,%12,%13,%14,%15,%16,%17,%18,%19,%20,%21,%22,%23,%24,%25,%26,%27,%28,%29,%30,%31,%32,%33,%34,%35,%36,%37,%38,%39,%40,%41,%42,%43,%44,%45,%46,%47,%48,%49,%50,%51,%52,%53,%54,%55,%56,%57,%58,%59,%60,%61,%62,%63,%64,%65,%66,%67,%68,%69,%70,%71,%72,%73,%74,%75}, dA, dB, pt, 1, 1, 0, 0;\n"
    "mov.b32 t, %76+518; mov.b32 u, %77+1286;\n"
    "mov.b64 dA, {t, hb}; mov.b64 dB, {u, hb};\n"
    "wgmma.mma_async.sync.aligned.m64n152k16.f32.bf16.bf16 {%0,%1,%2,%3,%4,%5,%6,%7,%8,%9,%10,%11,%12,%13,%14,%15,%16,%17,%18,%19,%20,%21,%22,%23,%24,%25,%26,%27,%28,%29,%30,%31,%32,%33,%34,%35,%36,%37,%38,%39,%40,%41,%42,%43,%44,%45,%46,%47,%48,%49,%50,%51,%52,%53,%54,%55,%56,%57,%58,%59,%60,%61,%62,%63,%64,%65,%66,%67,%68,%69,%70,%71,%72,%73,%74,%75}, dA, dB, pt, 1, 1, 0, 0;\n"
    "wgmma.commit_group.sync.aligned;\n"
    "mov.b32 t, %78+16;\n"
    "W2: mbarrier.try_wait.parity.shared::cta.b64 pw, [t], 0, 100000;\n"
    "@!pw bra W2;\n"
    "wgmma.fence.sync.aligned;\n"
    "mov.b32 t, %76+1024; mov.b32 u, %77+2560;\n"
    "mov.b64 dA, {t, hb}; mov.b64 dB, {u, hb};\n"
    "wgmma.mma_async.sync.aligned.m64n152k16.f32.bf16.bf16 {%0,%1,%2,%3,%4,%5,%6,%7,%8,%9,%10,%11,%12,%13,%14,%15,%16,%17,%18,%19,%20,%21,%22,%23,%24,%25,%26,%27,%28,%29,%30,%31,%32,%33,%34,%35,%36,%37,%38,%39,%40,%41,%42,%43,%44,%45,%46,%47,%48,%49,%50,%51,%52,%53,%54,%55,%56,%57,%58,%59,%60,%61,%62,%63,%64,%65,%66,%67,%68,%69,%70,%71,%72,%73,%74,%75}, dA, dB, pt, 1, 1, 0, 0;\n"
    "mov.b32 t, %76+1026; mov.b32 u, %77+2562;\n"
    "mov.b64 dA, {t, hb}; mov.b64 dB, {u, hb};\n"
    "wgmma.mma_async.sync.aligned.m64n152k16.f32.bf16.bf16 {%0,%1,%2,%3,%4,%5,%6,%7,%8,%9,%10,%11,%12,%13,%14,%15,%16,%17,%18,%19,%20,%21,%22,%23,%24,%25,%26,%27,%28,%29,%30,%31,%32,%33,%34,%35,%36,%37,%38,%39,%40,%41,%42,%43,%44,%45,%46,%47,%48,%49,%50,%51,%52,%53,%54,%55,%56,%57,%58,%59,%60,%61,%62,%63,%64,%65,%66,%67,%68,%69,%70,%71,%72,%73,%74,%75}, dA, dB, pt, 1, 1, 0, 0;\n"
    "wgmma.commit_group.sync.aligned;\n"
    "wgmma.wait_group.sync.aligned 1;\n"
    "mov.b32 t, %79+8;\n"
    "@pe mbarrier.arrive.shared::cta.b64 _, [t];\n"
    "mov.b32 t, %76+1028; mov.b32 u, %77+2564;\n"
    "mov.b64 dA, {t, hb}; mov.b64 dB, {u, hb};\n"
    "wgmma.mma_async.sync.aligned.m64n152k16.f32.bf16.bf16 {%0,%1,%2,%3,%4,%5,%6,%7,%8,%9,%10,%11,%12,%13,%14,%15,%16,%17,%18,%19,%20,%21,%22,%23,%24,%25,%26,%27,%28,%29,%30,%31,%32,%33,%34,%35,%36,%37,%38,%39,%40,%41,%42,%43,%44,%45,%46,%47,%48,%49,%50,%51,%52,%53,%54,%55,%56,%57,%58,%59,%60,%61,%62,%63,%64,%65,%66,%67,%68,%69,%70,%71,%72,%73,%74,%75}, dA, dB, pt, 1, 1, 0, 0;\n"
    "mov.b32 t, %76+1030; mov.b32 u, %77+2566;\n"
    "mov.b64 dA, {t, hb}; mov.b64 dB, {u, hb};\n"
    "wgmma.mma_async.sync.aligned.m64n152k16.f32.bf16.bf16 {%0,%1,%2,%3,%4,%5,%6,%7,%8,%9,%10,%11,%12,%13,%14,%15,%16,%17,%18,%19,%20,%21,%22,%23,%24,%25,%26,%27,%28,%29,%30,%31,%32,%33,%34,%35,%36,%37,%38,%39,%40,%41,%42,%43,%44,%45,%46,%47,%48,%49,%50,%51,%52,%53,%54,%55,%56,%57,%58,%59,%60,%61,%62,%63,%64,%65,%66,%67,%68,%69,%70,%71,%72,%73,%74,%75}, dA, dB, pt, 1, 1, 0, 0;\n"
    "wgmma.commit_group.sync.aligned;\n"
    "mov.b32 t, %78+24;\n"
    "W3: mbarrier.try_wait.parity.shared::cta.b64 pw, [t], 0, 100000;\n"
    "@!pw bra W3;\n"
    "wgmma.fence.sync.aligned;\n"
    "mov.b32 t, %76+1536; mov.b32 u, %77+3840;\n"
    "mov.b64 dA, {t, hb}; mov.b64 dB, {u, hb};\n"
    "wgmma.mma_async.sync.aligned.m64n152k16.f32.bf16.bf16 {%0,%1,%2,%3,%4,%5,%6,%7,%8,%9,%10,%11,%12,%13,%14,%15,%16,%17,%18,%19,%20,%21,%22,%23,%24,%25,%26,%27,%28,%29,%30,%31,%32,%33,%34,%35,%36,%37,%38,%39,%40,%41,%42,%43,%44,%45,%46,%47,%48,%49,%50,%51,%52,%53,%54,%55,%56,%57,%58,%59,%60,%61,%62,%63,%64,%65,%66,%67,%68,%69,%70,%71,%72,%73,%74,%75}, dA, dB, pt, 1, 1, 0, 0;\n"
    "mov.b32 t, %76+1538; mov.b32 u, %77+3842;\n"
    "mov.b64 dA, {t, hb}; mov.b64 dB, {u, hb};\n"
    "wgmma.mma_async.sync.aligned.m64n152k16.f32.bf16.bf16 {%0,%1,%2,%3,%4,%5,%6,%7,%8,%9,%10,%11,%12,%13,%14,%15,%16,%17,%18,%19,%20,%21,%22,%23,%24,%25,%26,%27,%28,%29,%30,%31,%32,%33,%34,%35,%36,%37,%38,%39,%40,%41,%42,%43,%44,%45,%46,%47,%48,%49,%50,%51,%52,%53,%54,%55,%56,%57,%58,%59,%60,%61,%62,%63,%64,%65,%66,%67,%68,%69,%70,%71,%72,%73,%74,%75}, dA, dB, pt, 1, 1, 0, 0;\n"
    "wgmma.commit_group.sync.aligned;\n"
    "wgmma.wait_group.sync.aligned 1;\n"
    "mov.b32 t, %79+16;\n"
    "@pe mbarrier.arrive.shared::cta.b64 _, [t];\n"
    "mov.b32 t, %76+1540; mov.b32 u, %77+3844;\n"
    "mov.b64 dA, {t, hb}; mov.b64 dB, {u, hb};\n"
    "wgmma.mma_async.sync.aligned.m64n152k16.f32.bf16.bf16 {%0,%1,%2,%3,%4,%5,%6,%7,%8,%9,%10,%11,%12,%13,%14,%15,%16,%17,%18,%19,%20,%21,%22,%23,%24,%25,%26,%27,%28,%29,%30,%31,%32,%33,%34,%35,%36,%37,%38,%39,%40,%41,%42,%43,%44,%45,%46,%47,%48,%49,%50,%51,%52,%53,%54,%55,%56,%57,%58,%59,%60,%61,%62,%63,%64,%65,%66,%67,%68,%69,%70,%71,%72,%73,%74,%75}, dA, dB, pt, 1, 1, 0, 0;\n"
    "mov.b32 t, %76+1542; mov.b32 u, %77+3846;\n"
    "mov.b64 dA, {t, hb}; mov.b64 dB, {u, hb};\n"
    "wgmma.mma_async.sync.aligned.m64n152k16.f32.bf16.bf16 {%0,%1,%2,%3,%4,%5,%6,%7,%8,%9,%10,%11,%12,%13,%14,%15,%16,%17,%18,%19,%20,%21,%22,%23,%24,%25,%26,%27,%28,%29,%30,%31,%32,%33,%34,%35,%36,%37,%38,%39,%40,%41,%42,%43,%44,%45,%46,%47,%48,%49,%50,%51,%52,%53,%54,%55,%56,%57,%58,%59,%60,%61,%62,%63,%64,%65,%66,%67,%68,%69,%70,%71,%72,%73,%74,%75}, dA, dB, pt, 1, 1, 0, 0;\n"
    "wgmma.commit_group.sync.aligned;\n"
    "mov.b32 t, %78+32;\n"
    "W4: mbarrier.try_wait.parity.shared::cta.b64 pw, [t], 0, 100000;\n"
    "@!pw bra W4;\n"
    "wgmma.fence.sync.aligned;\n"
    "mov.b32 t, %76+2048; mov.b32 u, %77+5120;\n"
    "mov.b64 dA, {t, hb}; mov.b64 dB, {u, hb};\n"
    "wgmma.mma_async.sync.aligned.m64n152k16.f32.bf16.bf16 {%0,%1,%2,%3,%4,%5,%6,%7,%8,%9,%10,%11,%12,%13,%14,%15,%16,%17,%18,%19,%20,%21,%22,%23,%24,%25,%26,%27,%28,%29,%30,%31,%32,%33,%34,%35,%36,%37,%38,%39,%40,%41,%42,%43,%44,%45,%46,%47,%48,%49,%50,%51,%52,%53,%54,%55,%56,%57,%58,%59,%60,%61,%62,%63,%64,%65,%66,%67,%68,%69,%70,%71,%72,%73,%74,%75}, dA, dB, pt, 1, 1, 0, 0;\n"
    "mov.b32 t, %76+2050; mov.b32 u, %77+5122;\n"
    "mov.b64 dA, {t, hb}; mov.b64 dB, {u, hb};\n"
    "wgmma.mma_async.sync.aligned.m64n152k16.f32.bf16.bf16 {%0,%1,%2,%3,%4,%5,%6,%7,%8,%9,%10,%11,%12,%13,%14,%15,%16,%17,%18,%19,%20,%21,%22,%23,%24,%25,%26,%27,%28,%29,%30,%31,%32,%33,%34,%35,%36,%37,%38,%39,%40,%41,%42,%43,%44,%45,%46,%47,%48,%49,%50,%51,%52,%53,%54,%55,%56,%57,%58,%59,%60,%61,%62,%63,%64,%65,%66,%67,%68,%69,%70,%71,%72,%73,%74,%75}, dA, dB, pt, 1, 1, 0, 0;\n"
    "wgmma.commit_group.sync.aligned;\n"
    "wgmma.wait_group.sync.aligned 1;\n"
    "mov.b32 t, %79+24;\n"
    "@pe mbarrier.arrive.shared::cta.b64 _, [t];\n"
    "mov.b32 t, %76+2052; mov.b32 u, %77+5124;\n"
    "mov.b64 dA, {t, hb}; mov.b64 dB, {u, hb};\n"
    "wgmma.mma_async.sync.aligned.m64n152k16.f32.bf16.bf16 {%0,%1,%2,%3,%4,%5,%6,%7,%8,%9,%10,%11,%12,%13,%14,%15,%16,%17,%18,%19,%20,%21,%22,%23,%24,%25,%26,%27,%28,%29,%30,%31,%32,%33,%34,%35,%36,%37,%38,%39,%40,%41,%42,%43,%44,%45,%46,%47,%48,%49,%50,%51,%52,%53,%54,%55,%56,%57,%58,%59,%60,%61,%62,%63,%64,%65,%66,%67,%68,%69,%70,%71,%72,%73,%74,%75}, dA, dB, pt, 1, 1, 0, 0;\n"
    "mov.b32 t, %76+2054; mov.b32 u, %77+5126;\n"
    "mov.b64 dA, {t, hb}; mov.b64 dB, {u, hb};\n"
    "wgmma.mma_async.sync.aligned.m64n152k16.f32.bf16.bf16 {%0,%1,%2,%3,%4,%5,%6,%7,%8,%9,%10,%11,%12,%13,%14,%15,%16,%17,%18,%19,%20,%21,%22,%23,%24,%25,%26,%27,%28,%29,%30,%31,%32,%33,%34,%35,%36,%37,%38,%39,%40,%41,%42,%43,%44,%45,%46,%47,%48,%49,%50,%51,%52,%53,%54,%55,%56,%57,%58,%59,%60,%61,%62,%63,%64,%65,%66,%67,%68,%69,%70,%71,%72,%73,%74,%75}, dA, dB, pt, 1, 1, 0, 0;\n"
    "wgmma.commit_group.sync.aligned;\n"
    "mov.b32 t, %78+0;\n"
    "W5: mbarrier.try_wait.parity.shared::cta.b64 pw, [t], 1, 100000;\n"
    "@!pw bra W5;\n"
    "wgmma.fence.sync.aligned;\n"
    "mov.b32 t, %76+2560; mov.b32 u, %77+0;\n"
    "mov.b64 dA, {t, hb}; mov.b64 dB, {u, hb};\n"
    "wgmma.mma_async.sync.aligned.m64n152k16.f32.bf16.bf16 {%0,%1,%2,%3,%4,%5,%6,%7,%8,%9,%10,%11,%12,%13,%14,%15,%16,%17,%18,%19,%20,%21,%22,%23,%24,%25,%26,%27,%28,%29,%30,%31,%32,%33,%34,%35,%36,%37,%38,%39,%40,%41,%42,%43,%44,%45,%46,%47,%48,%49,%50,%51,%52,%53,%54,%55,%56,%57,%58,%59,%60,%61,%62,%63,%64,%65,%66,%67,%68,%69,%70,%71,%72,%73,%74,%75}, dA, dB, pt, 1, 1, 0, 0;\n"
    "mov.b32 t, %76+2562; mov.b32 u, %77+2;\n"
    "mov.b64 dA, {t, hb}; mov.b64 dB, {u, hb};\n"
    "wgmma.mma_async.sync.aligned.m64n152k16.f32.bf16.bf16 {%0,%1,%2,%3,%4,%5,%6,%7,%8,%9,%10,%11,%12,%13,%14,%15,%16,%17,%18,%19,%20,%21,%22,%23,%24,%25,%26,%27,%28,%29,%30,%31,%32,%33,%34,%35,%36,%37,%38,%39,%40,%41,%42,%43,%44,%45,%46,%47,%48,%49,%50,%51,%52,%53,%54,%55,%56,%57,%58,%59,%60,%61,%62,%63,%64,%65,%66,%67,%68,%69,%70,%71,%72,%73,%74,%75}, dA, dB, pt, 1, 1, 0, 0;\n"
    "wgmma.commit_group.sync.aligned;\n"
    "wgmma.wait_group.sync.aligned 1;\n"
    "mov.b32 t, %79+32;\n"
    "@pe mbarrier.arrive.shared::cta.b64 _, [t];\n"
    "mov.b32 t, %76+2564; mov.b32 u, %77+4;\n"
    "mov.b64 dA, {t, hb}; mov.b64 dB, {u, hb};\n"
    "wgmma.mma_async.sync.aligned.m64n152k16.f32.bf16.bf16 {%0,%1,%2,%3,%4,%5,%6,%7,%8,%9,%10,%11,%12,%13,%14,%15,%16,%17,%18,%19,%20,%21,%22,%23,%24,%25,%26,%27,%28,%29,%30,%31,%32,%33,%34,%35,%36,%37,%38,%39,%40,%41,%42,%43,%44,%45,%46,%47,%48,%49,%50,%51,%52,%53,%54,%55,%56,%57,%58,%59,%60,%61,%62,%63,%64,%65,%66,%67,%68,%69,%70,%71,%72,%73,%74,%75}, dA, dB, pt, 1, 1, 0, 0;\n"
    "mov.b32 t, %76+2566; mov.b32 u, %77+6;\n"
    "mov.b64 dA, {t, hb}; mov.b64 dB, {u, hb};\n"
    "wgmma.mma_async.sync.aligned.m64n152k16.f32.bf16.bf16 {%0,%1,%2,%3,%4,%5,%6,%7,%8,%9,%10,%11,%12,%13,%14,%15,%16,%17,%18,%19,%20,%21,%22,%23,%24,%25,%26,%27,%28,%29,%30,%31,%32,%33,%34,%35,%36,%37,%38,%39,%40,%41,%42,%43,%44,%45,%46,%47,%48,%49,%50,%51,%52,%53,%54,%55,%56,%57,%58,%59,%60,%61,%62,%63,%64,%65,%66,%67,%68,%69,%70,%71,%72,%73,%74,%75}, dA, dB, pt, 1, 1, 0, 0;\n"
    "wgmma.commit_group.sync.aligned;\n"
    "mov.b32 t, %78+8;\n"
    "W6: mbarrier.try_wait.parity.shared::cta.b64 pw, [t], 1, 100000;\n"
    "@!pw bra W6;\n"
    "wgmma.fence.sync.aligned;\n"
    "mov.b32 t, %76+3072; mov.b32 u, %77+1280;\n"
    "mov.b64 dA, {t, hb}; mov.b64 dB, {u, hb};\n"
    "wgmma.mma_async.sync.aligned.m64n152k16.f32.bf16.bf16 {%0,%1,%2,%3,%4,%5,%6,%7,%8,%9,%10,%11,%12,%13,%14,%15,%16,%17,%18,%19,%20,%21,%22,%23,%24,%25,%26,%27,%28,%29,%30,%31,%32,%33,%34,%35,%36,%37,%38,%39,%40,%41,%42,%43,%44,%45,%46,%47,%48,%49,%50,%51,%52,%53,%54,%55,%56,%57,%58,%59,%60,%61,%62,%63,%64,%65,%66,%67,%68,%69,%70,%71,%72,%73,%74,%75}, dA, dB, pt, 1, 1, 0, 0;\n"
    "mov.b32 t, %76+3074; mov.b32 u, %77+1282;\n"
    "mov.b64 dA, {t, hb}; mov.b64 dB, {u, hb};\n"
    "wgmma.mma_async.sync.aligned.m64n152k16.f32.bf16.bf16 {%0,%1,%2,%3,%4,%5,%6,%7,%8,%9,%10,%11,%12,%13,%14,%15,%16,%17,%18,%19,%20,%21,%22,%23,%24,%25,%26,%27,%28,%29,%30,%31,%32,%33,%34,%35,%36,%37,%38,%39,%40,%41,%42,%43,%44,%45,%46,%47,%48,%49,%50,%51,%52,%53,%54,%55,%56,%57,%58,%59,%60,%61,%62,%63,%64,%65,%66,%67,%68,%69,%70,%71,%72,%73,%74,%75}, dA, dB, pt, 1, 1, 0, 0;\n"
    "wgmma.commit_group.sync.aligned;\n"
    "wgmma.wait_group.sync.aligned 1;\n"
    "mov.b32 t, %79+0;\n"
    "@pe mbarrier.arrive.shared::cta.b64 _, [t];\n"
    "mov.b32 t, %76+3076; mov.b32 u, %77+1284;\n"
    "mov.b64 dA, {t, hb}; mov.b64 dB, {u, hb};\n"
    "wgmma.mma_async.sync.aligned.m64n152k16.f32.bf16.bf16 {%0,%1,%2,%3,%4,%5,%6,%7,%8,%9,%10,%11,%12,%13,%14,%15,%16,%17,%18,%19,%20,%21,%22,%23,%24,%25,%26,%27,%28,%29,%30,%31,%32,%33,%34,%35,%36,%37,%38,%39,%40,%41,%42,%43,%44,%45,%46,%47,%48,%49,%50,%51,%52,%53,%54,%55,%56,%57,%58,%59,%60,%61,%62,%63,%64,%65,%66,%67,%68,%69,%70,%71,%72,%73,%74,%75}, dA, dB, pt, 1, 1, 0, 0;\n"
    "mov.b32 t, %76+3078; mov.b32 u, %77+1286;\n"
    "mov.b64 dA, {t, hb}; mov.b64 dB, {u, hb};\n"
    "wgmma.mma_async.sync.aligned.m64n152k16.f32.bf16.bf16 {%0,%1,%2,%3,%4,%5,%6,%7,%8,%9,%10,%11,%12,%13,%14,%15,%16,%17,%18,%19,%20,%21,%22,%23,%24,%25,%26,%27,%28,%29,%30,%31,%32,%33,%34,%35,%36,%37,%38,%39,%40,%41,%42,%43,%44,%45,%46,%47,%48,%49,%50,%51,%52,%53,%54,%55,%56,%57,%58,%59,%60,%61,%62,%63,%64,%65,%66,%67,%68,%69,%70,%71,%72,%73,%74,%75}, dA, dB, pt, 1, 1, 0, 0;\n"
    "wgmma.commit_group.sync.aligned;\n"
    "mov.b32 t, %78+16;\n"
    "W7: mbarrier.try_wait.parity.shared::cta.b64 pw, [t], 1, 100000;\n"
    "@!pw bra W7;\n"
    "wgmma.fence.sync.aligned;\n"
    "mov.b32 t, %76+3584; mov.b32 u, %77+2560;\n"
    "mov.b64 dA, {t, hb}; mov.b64 dB, {u, hb};\n"
    "wgmma.mma_async.sync.aligned.m64n152k16.f32.bf16.bf16 {%0,%1,%2,%3,%4,%5,%6,%7,%8,%9,%10,%11,%12,%13,%14,%15,%16,%17,%18,%19,%20,%21,%22,%23,%24,%25,%26,%27,%28,%29,%30,%31,%32,%33,%34,%35,%36,%37,%38,%39,%40,%41,%42,%43,%44,%45,%46,%47,%48,%49,%50,%51,%52,%53,%54,%55,%56,%57,%58,%59,%60,%61,%62,%63,%64,%65,%66,%67,%68,%69,%70,%71,%72,%73,%74,%75}, dA, dB, pt, 1, 1, 0, 0;\n"
    "mov.b32 t, %76+3586; mov.b32 u, %77+2562;\n"
    "mov.b64 dA, {t, hb}; mov.b64 dB, {u, hb};\n"
    "wgmma.mma_async.sync.aligned.m64n152k16.f32.bf16.bf16 {%0,%1,%2,%3,%4,%5,%6,%7,%8,%9,%10,%11,%12,%13,%14,%15,%16,%17,%18,%19,%20,%21,%22,%23,%24,%25,%26,%27,%28,%29,%30,%31,%32,%33,%34,%35,%36,%37,%38,%39,%40,%41,%42,%43,%44,%45,%46,%47,%48,%49,%50,%51,%52,%53,%54,%55,%56,%57,%58,%59,%60,%61,%62,%63,%64,%65,%66,%67,%68,%69,%70,%71,%72,%73,%74,%75}, dA, dB, pt, 1, 1, 0, 0;\n"
    "wgmma.commit_group.sync.aligned;\n"
    "wgmma.wait_group.sync.aligned 1;\n"
    "mov.b32 t, %79+8;\n"
    "@pe mbarrier.arrive.shared::cta.b64 _, [t];\n"
    "mov.b32 t, %76+3588; mov.b32 u, %77+2564;\n"
    "mov.b64 dA, {t, hb}; mov.b64 dB, {u, hb};\n"
    "wgmma.mma_async.sync.aligned.m64n152k16.f32.bf16.bf16 {%0,%1,%2,%3,%4,%5,%6,%7,%8,%9,%10,%11,%12,%13,%14,%15,%16,%17,%18,%19,%20,%21,%22,%23,%24,%25,%26,%27,%28,%29,%30,%31,%32,%33,%34,%35,%36,%37,%38,%39,%40,%41,%42,%43,%44,%45,%46,%47,%48,%49,%50,%51,%52,%53,%54,%55,%56,%57,%58,%59,%60,%61,%62,%63,%64,%65,%66,%67,%68,%69,%70,%71,%72,%73,%74,%75}, dA, dB, pt, 1, 1, 0, 0;\n"
    "mov.b32 t, %76+3590; mov.b32 u, %77+2566;\n"
    "mov.b64 dA, {t, hb}; mov.b64 dB, {u, hb};\n"
    "wgmma.mma_async.sync.aligned.m64n152k16.f32.bf16.bf16 {%0,%1,%2,%3,%4,%5,%6,%7,%8,%9,%10,%11,%12,%13,%14,%15,%16,%17,%18,%19,%20,%21,%22,%23,%24,%25,%26,%27,%28,%29,%30,%31,%32,%33,%34,%35,%36,%37,%38,%39,%40,%41,%42,%43,%44,%45,%46,%47,%48,%49,%50,%51,%52,%53,%54,%55,%56,%57,%58,%59,%60,%61,%62,%63,%64,%65,%66,%67,%68,%69,%70,%71,%72,%73,%74,%75}, dA, dB, pt, 1, 1, 0, 0;\n"
    "wgmma.commit_group.sync.aligned;\n"
    "mov.b32 t, %78+24;\n"
    "W8: mbarrier.try_wait.parity.shared::cta.b64 pw, [t], 1, 100000;\n"
    "@!pw bra W8;\n"
    "wgmma.fence.sync.aligned;\n"
    "mov.b32 t, %76+4096; mov.b32 u, %77+3840;\n"
    "mov.b64 dA, {t, hb}; mov.b64 dB, {u, hb};\n"
    "wgmma.mma_async.sync.aligned.m64n152k16.f32.bf16.bf16 {%0,%1,%2,%3,%4,%5,%6,%7,%8,%9,%10,%11,%12,%13,%14,%15,%16,%17,%18,%19,%20,%21,%22,%23,%24,%25,%26,%27,%28,%29,%30,%31,%32,%33,%34,%35,%36,%37,%38,%39,%40,%41,%42,%43,%44,%45,%46,%47,%48,%49,%50,%51,%52,%53,%54,%55,%56,%57,%58,%59,%60,%61,%62,%63,%64,%65,%66,%67,%68,%69,%70,%71,%72,%73,%74,%75}, dA, dB, pt, 1, 1, 0, 0;\n"
    "mov.b32 t, %76+4098; mov.b32 u, %77+3842;\n"
    "mov.b64 dA, {t, hb}; mov.b64 dB, {u, hb};\n"
    "wgmma.mma_async.sync.aligned.m64n152k16.f32.bf16.bf16 {%0,%1,%2,%3,%4,%5,%6,%7,%8,%9,%10,%11,%12,%13,%14,%15,%16,%17,%18,%19,%20,%21,%22,%23,%24,%25,%26,%27,%28,%29,%30,%31,%32,%33,%34,%35,%36,%37,%38,%39,%40,%41,%42,%43,%44,%45,%46,%47,%48,%49,%50,%51,%52,%53,%54,%55,%56,%57,%58,%59,%60,%61,%62,%63,%64,%65,%66,%67,%68,%69,%70,%71,%72,%73,%74,%75}, dA, dB, pt, 1, 1, 0, 0;\n"
    "wgmma.commit_group.sync.aligned;\n"
    "wgmma.wait_group.sync.aligned 1;\n"
    "mov.b32 t, %79+16;\n"
    "@pe mbarrier.arrive.shared::cta.b64 _, [t];\n"
    "mov.b32 t, %76+4100; mov.b32 u, %77+3844;\n"
    "mov.b64 dA, {t, hb}; mov.b64 dB, {u, hb};\n"
    "wgmma.mma_async.sync.aligned.m64n152k16.f32.bf16.bf16 {%0,%1,%2,%3,%4,%5,%6,%7,%8,%9,%10,%11,%12,%13,%14,%15,%16,%17,%18,%19,%20,%21,%22,%23,%24,%25,%26,%27,%28,%29,%30,%31,%32,%33,%34,%35,%36,%37,%38,%39,%40,%41,%42,%43,%44,%45,%46,%47,%48,%49,%50,%51,%52,%53,%54,%55,%56,%57,%58,%59,%60,%61,%62,%63,%64,%65,%66,%67,%68,%69,%70,%71,%72,%73,%74,%75}, dA, dB, pt, 1, 1, 0, 0;\n"
    "mov.b32 t, %76+4102; mov.b32 u, %77+3846;\n"
    "mov.b64 dA, {t, hb}; mov.b64 dB, {u, hb};\n"
    "wgmma.mma_async.sync.aligned.m64n152k16.f32.bf16.bf16 {%0,%1,%2,%3,%4,%5,%6,%7,%8,%9,%10,%11,%12,%13,%14,%15,%16,%17,%18,%19,%20,%21,%22,%23,%24,%25,%26,%27,%28,%29,%30,%31,%32,%33,%34,%35,%36,%37,%38,%39,%40,%41,%42,%43,%44,%45,%46,%47,%48,%49,%50,%51,%52,%53,%54,%55,%56,%57,%58,%59,%60,%61,%62,%63,%64,%65,%66,%67,%68,%69,%70,%71,%72,%73,%74,%75}, dA, dB, pt, 1, 1, 0, 0;\n"
    "wgmma.commit_group.sync.aligned;\n"
    "mov.b32 t, %78+32;\n"
    "W9: mbarrier.try_wait.parity.shared::cta.b64 pw, [t], 1, 100000;\n"
    "@!pw bra W9;\n"
    "wgmma.fence.sync.aligned;\n"
    "mov.b32 t, %76+4608; mov.b32 u, %77+5120;\n"
    "mov.b64 dA, {t, hb}; mov.b64 dB, {u, hb};\n"
    "wgmma.mma_async.sync.aligned.m64n152k16.f32.bf16.bf16 {%0,%1,%2,%3,%4,%5,%6,%7,%8,%9,%10,%11,%12,%13,%14,%15,%16,%17,%18,%19,%20,%21,%22,%23,%24,%25,%26,%27,%28,%29,%30,%31,%32,%33,%34,%35,%36,%37,%38,%39,%40,%41,%42,%43,%44,%45,%46,%47,%48,%49,%50,%51,%52,%53,%54,%55,%56,%57,%58,%59,%60,%61,%62,%63,%64,%65,%66,%67,%68,%69,%70,%71,%72,%73,%74,%75}, dA, dB, pt, 1, 1, 0, 0;\n"
    "mov.b32 t, %76+4610; mov.b32 u, %77+5122;\n"
    "mov.b64 dA, {t, hb}; mov.b64 dB, {u, hb};\n"
    "wgmma.mma_async.sync.aligned.m64n152k16.f32.bf16.bf16 {%0,%1,%2,%3,%4,%5,%6,%7,%8,%9,%10,%11,%12,%13,%14,%15,%16,%17,%18,%19,%20,%21,%22,%23,%24,%25,%26,%27,%28,%29,%30,%31,%32,%33,%34,%35,%36,%37,%38,%39,%40,%41,%42,%43,%44,%45,%46,%47,%48,%49,%50,%51,%52,%53,%54,%55,%56,%57,%58,%59,%60,%61,%62,%63,%64,%65,%66,%67,%68,%69,%70,%71,%72,%73,%74,%75}, dA, dB, pt, 1, 1, 0, 0;\n"
    "wgmma.commit_group.sync.aligned;\n"
    "wgmma.wait_group.sync.aligned 1;\n"
    "mov.b32 t, %79+24;\n"
    "@pe mbarrier.arrive.shared::cta.b64 _, [t];\n"
    "@pe mbarrier.arrive.shared::cta.b64 _, [%81];\n"
    "mov.b32 t, %76+4612; mov.b32 u, %77+5124;\n"
    "mov.b64 dA, {t, hb}; mov.b64 dB, {u, hb};\n"
    "wgmma.mma_async.sync.aligned.m64n152k16.f32.bf16.bf16 {%0,%1,%2,%3,%4,%5,%6,%7,%8,%9,%10,%11,%12,%13,%14,%15,%16,%17,%18,%19,%20,%21,%22,%23,%24,%25,%26,%27,%28,%29,%30,%31,%32,%33,%34,%35,%36,%37,%38,%39,%40,%41,%42,%43,%44,%45,%46,%47,%48,%49,%50,%51,%52,%53,%54,%55,%56,%57,%58,%59,%60,%61,%62,%63,%64,%65,%66,%67,%68,%69,%70,%71,%72,%73,%74,%75}, dA, dB, pt, 1, 1, 0, 0;\n"
    "mov.b32 t, %76+4614; mov.b32 u, %77+5126;\n"
    "mov.b64 dA, {t, hb}; mov.b64 dB, {u, hb};\n"
    "wgmma.mma_async.sync.aligned.m64n152k16.f32.bf16.bf16 {%0,%1,%2,%3,%4,%5,%6,%7,%8,%9,%10,%11,%12,%13,%14,%15,%16,%17,%18,%19,%20,%21,%22,%23,%24,%25,%26,%27,%28,%29,%30,%31,%32,%33,%34,%35,%36,%37,%38,%39,%40,%41,%42,%43,%44,%45,%46,%47,%48,%49,%50,%51,%52,%53,%54,%55,%56,%57,%58,%59,%60,%61,%62,%63,%64,%65,%66,%67,%68,%69,%70,%71,%72,%73,%74,%75}, dA, dB, pt, 1, 1, 0, 0;\n"
    "wgmma.commit_group.sync.aligned;\n"
    "}\n"
    : "=f"(d[0]),"=f"(d[1]),"=f"(d[2]),"=f"(d[3]),"=f"(d[4]),"=f"(d[5]),"=f"(d[6]),"=f"(d[7]),"=f"(d[8]),"=f"(d[9]),"=f"(d[10]),"=f"(d[11]),"=f"(d[12]),"=f"(d[13]),"=f"(d[14]),"=f"(d[15]),"=f"(d[16]),"=f"(d[17]),"=f"(d[18]),"=f"(d[19]),"=f"(d[20]),"=f"(d[21]),"=f"(d[22]),"=f"(d[23]),"=f"(d[24]),"=f"(d[25]),"=f"(d[26]),"=f"(d[27]),"=f"(d[28]),"=f"(d[29]),"=f"(d[30]),"=f"(d[31]),"=f"(d[32]),"=f"(d[33]),"=f"(d[34]),"=f"(d[35]),"=f"(d[36]),"=f"(d[37]),"=f"(d[38]),"=f"(d[39]),"=f"(d[40]),"=f"(d[41]),"=f"(d[42]),"=f"(d[43]),"=f"(d[44]),"=f"(d[45]),"=f"(d[46]),"=f"(d[47]),"=f"(d[48]),"=f"(d[49]),"=f"(d[50]),"=f"(d[51]),"=f"(d[52]),"=f"(d[53]),"=f"(d[54]),"=f"(d[55]),"=f"(d[56]),"=f"(d[57]),"=f"(d[58]),"=f"(d[59]),"=f"(d[60]),"=f"(d[61]),"=f"(d[62]),"=f"(d[63]),"=f"(d[64]),"=f"(d[65]),"=f"(d[66]),"=f"(d[67]),"=f"(d[68]),"=f"(d[69]),"=f"(d[70]),"=f"(d[71]),"=f"(d[72]),"=f"(d[73]),"=f"(d[74]),"=f"(d[75])
    : "n"(desc_lo(A_X, 16)), "n"(desc_lo(A_RING, 16)), "n"(BAR_FULL), "n"(BAR_EMPTY), "n"(kHiSw128), "r"(tok)
    : "memory");
}
__device__ __forceinline__ void a_mainloop160(float* d, uint32_t da, uint32_t ph, int n, uint32_t xw, uint32_t tok) {
  asm volatile(
    "{ .reg .pred pe, pw, pl, ps, pt; .reg .b32 da, ha, hb, ph, n, xw, pa, fb, t, u; .reg .b64 dA, dB;\n"
    "mov.b32 da, %80; mov.b32 ph, %81; mov.b32 n, %82; mov.b32 xw, %83; mov.b32 fb, %85; mov.b32 pa, %87; mov.b32 hb, %88; mov.b32 ha, %89;\n"
    "mov.u32 t, %%laneid; setp.lt.u32 pe, t, 2; setp.eq.b32 ps, 0, 0; setp.eq.b32 pt, 0, 0;\n"
    "LOOP:\n"
    "X0: mbarrier.try_wait.parity.shared::cta.b64 pw, [xw+-24], 0, 100000;\n"
    "@!pw bra X0;\n"
    "W0: mbarrier.try_wait.parity.shared::cta.b64 pw, [fb+0], ph, 100000;\n"
    "@!pw bra W0;\n"
    "wgmma.fence.sync.aligned;\n"
    "add.u32 t, da, 0; mov.b32 u, %84+0;\n"
    "mov.b64 dA, {t, ha}; mov.b64 dB, {u, hb};\n"
    "wgmma.mma_async.sync.aligned.m64n160k16.f32.bf16.bf16 {%0,%1,%2,%3,%4,%5,%6,%7,%8,%9,%10,%11,%12,%13,%14,%15,%16,%17,%18,%19,%20,%21,%22,%23,%24,%25,%26,%27,%28,%29,%30,%31,%32,%33,%34,%35,%36,%37,%38,%39,%40,%41,%42,%43,%44,%45,%46,%47,%48,%49,%50,%51,%52,%53,%54,%55,%56,%57,%58,%59,%60,%61,%62,%63,%64,%65,%66,%67,%68,%69,%70,%71,%72,%73,%74,%75,%76,%77,%78,%79}, dA, dB, ps, 1, 1, 0, 0;\n"
    "add.u32 t, da, 128; mov.b32 u, %84+2;\n"
    "mov.b64 dA, {t, ha}; mov.b64 dB, {u, hb};\n"
    "wgmma.mma_async.sync.aligned.m64n160k16.f32.bf16.bf16 {%0,%1,%2,%3,%4,%5,%6,%7,%8,%9,%10,%11,%12,%13,%14,%15,%16,%17,%18,%19,%20,%21,%22,%23,%24,%25,%26,%27,%28,%29,%30,%31,%32,%33,%34,%35,%36,%37,%38,%39,%40,%41,%42,%43,%44,%45,%46,%47,%48,%49,%50,%51,%52,%53,%54,%55,%56,%57,%58,%59,%60,%61,%62,%63,%64,%65,%66,%67,%68,%69,%70,%71,%72,%73,%74,%75,%76,%77,%78,%79}, dA, dB, pt, 1, 1, 0, 0;\n"
    "wgmma.commit_group.sync.aligned;\n"
    "wgmma.wait_group.sync.aligned 1;\n"
    "@pe mbarrier.arrive.shared::cta.b64 _, [pa];\n"
    "add.u32 t, da, 256; mov.b32 u, %84+4;\n"
    "mov.b64 dA, {t, ha}; mov.b64 dB, {u, hb};\n"
    "wgmma.mma_async.sync.aligned.m64n160k16.f32.bf16.bf16 {%0,%1,%2,%3,%4,%5,%6,%7,%8,%9,%10,%11,%12,%13,%14,%15,%16,%17,%18,%19,%20,%21,%22,%23,%24,%25,%26,%27,%28,%29,%30,%31,%32,%33,%34,%35,%36,%37,%38,%39,%40,%41,%42,%43,%44,%45,%46,%47,%48,%49,%50,%51,%52,%53,%54,%55,%56,%57,%58,%59,%60,%61,%62,%63,%64,%65,%66,%67,%68,%69,%70,%71,%72,%73,%74,%75,%76,%77,%78,%79}, dA, dB, pt, 1, 1, 0, 0;\n"
    "add.u32 t, da, 384; mov.b32 u, %84+6;\n"
    "mov.b64 dA, {t, ha}; mov.b64 dB, {u, hb};\n"
    "wgmma.mma_async.sync.aligned.m64n160k16.f32.bf16.bf16 {%0,%1,%2,%3,%4,%5,%6,%7,%8,%9,%10,%11,%12,%13,%14,%15,%16,%17,%18,%19,%20,%21,%22,%23,%24,%25,%26,%27,%28,%29,%30,%31,%32,%33,%34,%35,%36,%37,%38,%39,%40,%41,%42,%43,%44,%45,%46,%47,%48,%49,%50,%51,%52,%53,%54,%55,%56,%57,%58,%59,%60,%61,%62,%63,%64,%65,%66,%67,%68,%69,%70,%71,%72,%73,%74,%75,%76,%77,%78,%79}, dA, dB, pt, 1, 1, 0, 0;\n"
    "wgmma.commit_group.sync.aligned;\n"
    "W1: mbarrier.try_wait.parity.shared::cta.b64 pw, [fb+8], ph, 100000;\n"
    "@!pw bra W1;\n"
    "wgmma.fence.sync.aligned;\n"
    "add.u32 t, da, 512; mov.b32 u, %84+1280;\n"
    "mov.b64 dA, {t, ha}; mov.b64 dB, {u, hb};\n"
    "wgmma.mma_async.sync.aligned.m64n160k16.f32.bf16.bf16 {%0,%1,%2,%3,%4,%5,%6,%7,%8,%9,%10,%11,%12,%13,%14,%15,%16,%17,%18,%19,%20,%21,%22,%23,%24,%25,%26,%27,%28,%29,%30,%31,%32,%33,%34,%35,%36,%37,%38,%39,%40,%41,%42,%43,%44,%45,%46,%47,%48,%49,%50,%51,%52,%53,%54,%55,%56,%57,%58,%59,%60,%61,%62,%63,%64,%65,%66,%67,%68,%69,%70,%71,%72,%73,%74,%75,%76,%77,%78,%79}, dA, dB, pt, 1, 1, 0, 0;\n"
    "add.u32 t, da, 640; mov.b32 u, %84+1282;\n"
    "mov.b64 dA, {t, ha}; mov.b64 dB, {u, hb};\n"
    "wgmma.mma_async.sync.aligned.m64n160k16.f32.bf16.bf16 {%0,%1,%2,%3,%4,%5,%6,%7,%8,%9,%10,%11,%12,%13,%14,%15,%16,%17,%18,%19,%20,%21,%22,%23,%24,%25,%26,%27,%28,%29,%30,%31,%32,%33,%34,%35,%36,%37,%38,%39,%40,%41,%42,%43,%44,%45,%46,%47,%48,%49,%50,%51,%52,%53,%54,%55,%56,%57,%58,%59,%60,%61,%62,%63,%64,%65,%66,%67,%68,%69,%70,%71,%72,%73,%74,%75,%76,%77,%78,%79}, dA, dB, pt, 1, 1, 0, 0;\n"
    "wgmma.commit_group.sync.aligned;\n"
    "wgmma.wait_group.sync.aligned 1;\n"
    "@pe mbarrier.arrive.shared::cta.b64 _, [fb+%86+0];\n"
    "add.u32 t, da, 768; mov.b32 u, %84+1284;\n"
    "mov.b64 dA, {t, ha}; mov.b64 dB, {u, hb};\n"
    "wgmma.mma_async.sync.aligned.m64n160k16.f32.bf16.bf16 {%0,%1,%2,%3,%4,%5,%6,%7,%8,%9,%10,%11,%12,%13,%14,%15,%16,%17,%18,%19,%20,%21,%22,%23,%24,%25,%26,%27,%28,%29,%30,%31,%32,%33,%34,%35,%36,%37,%38,%39,%40,%41,%42,%43,%44,%45,%46,%47,%48,%49,%50,%51,%52,%53,%54,%55,%56,%57,%58,%59,%60,%61,%62,%63,%64,%65,%66,%67,%68,%69,%70,%71,%72,%73,%74,%75,%76,%77,%78,%79}, dA, dB, pt, 1, 1, 0, 0;\n"
    "add.u32 t, da, 896; mov.b32 u, %84+1286;\n"
    "mov.b64 dA, {t, ha}; mov.b64 dB, {u, hb};\n"
    "wgmma.mma_async.sync.aligned.m64n160k16.f32.bf16.bf16 {%0,%1,%2,%3,%4,%5,%6,%7,%8,%9,%10,%11,%12,%13,%14,%15,%16,%17,%18,%19,%20,%21,%22,%23,%24,%25,%26,%27,%28,%29,%30,%31,%32,%33,%34,%35,%36,%37,%38,%39,%40,%41,%42,%43,%44,%45,%46,%47,%48,%49,%50,%51,%52,%53,%54,%55,%56,%57,%58,%59,%60,%61,%62,%63,%64,%65,%66,%67,%68,%69,%70,%71,%72,%73,%74,%75,%76,%77,%78,%79}, dA, dB, pt, 1, 1, 0, 0;\n"
    "wgmma.commit_group.sync.aligned;\n"
    "W2: mbarrier.try_wait.parity.shared::cta.b64 pw, [fb+16], ph, 100000;\n"
    "@!pw bra W2;\n"
    "wgmma.fence.sync.aligned;\n"
    "add.u32 t, da, 1024; mov.b32 u, %84+2560;\n"
    "mov.b64 dA, {t, ha}; mov.b64 dB, {u, hb};\n"
    "wgmma.mma_async.sync.aligned.m64n160k16.f32.bf16.bf16 {%0,%1,%2,%3,%4,%5,%6,%7,%8,%9,%10,%11,%12,%13,%14,%15,%16,%17,%18,%19,%20,%21,%22,%23,%24,%25,%26,%27,%28,%29,%30,%31,%32,%33,%34,%35,%36,%37,%38,%39,%40,%41,%42,%43,%44,%45,%46,%47,%48,%49,%50,%51,%52,%53,%54,%55,%56,%57,%58,%59,%60,%61,%62,%63,%64,%65,%66,%67,%68,%69,%70,%71,%72,%73,%74,%75,%76,%77,%78,%79}, dA, dB, pt, 1, 1, 0, 0;\n"
    "add.u32 t, da, 1152; mov.b32 u, %84+2562;\n"
    "mov.b64 dA, {t, ha}; mov.b64 dB, {u, hb};\n"
    "wgmma.mma_async.sync.aligned.m64n160k16.f32.bf16.bf16 {%0,%1,%2,%3,%4,%5,%6,%7,%8,%9,%10,%11,%12,%13,%14,%15,%16,%17,%18,%19,%20,%21,%22,%23,%24,%25,%26,%27,%28,%29,%30,%31,%32,%33,%34,%35,%36,%37,%38,%39,%40,%41,%42,%43,%44,%45,%46,%47,%48,%49,%50,%51,%52,%53,%54,%55,%56,%57,%58,%59,%60,%61,%62,%63,%64,%65,%66,%67,%68,%69,%70,%71,%72,%73,%74,%75,%76,%77,%78,%79}, dA, dB, pt, 1, 1, 0, 0;\n"
    "wgmma.commit_group.sync.aligned;\n"
    "wgmma.wait_group.sync.aligned 1;\n"
    "@pe mbarrier.arrive.shared::cta.b64 _, [fb+%86+8];\n"
    "X2: mbarrier.try_wait.parity.shared::cta.b64 pw, [xw], 0, 100000;\n"
    "@!pw bra X2;\n"
    "wgmma.fence.sync.aligned;\n"
    "add.u32 t, da, 1280; mov.b32 u, %84+2564;\n"
    "mov.b64 dA, {t, ha}; mov.b64 dB, {u, hb};\n"
    "wgmma.mma_async.sync.aligned.m64n160k16.f32.bf16.bf16 {%0,%1,%2,%3,%4,%5,%6,%7,%8,%9,%10,%11,%12,%13,%14,%15,%16,%17,%18,%19,%20,%21,%22,%23,%24,%25,%26,%27,%28,%29,%30,%31,%32,%33,%34,%35,%36,%37,%38,%39,%40,%41,%42,%43,%44,%45,%46,%47,%48,%49,%50,%51,%52,%53,%54,%55,%56,%57,%58,%59,%60,%61,%62,%63,%64,%65,%66,%67,%68,%69,%70,%71,%72,%73,%74,%75,%76,%77,%78,%79}, dA, dB, pt, 1, 1, 0, 0;\n"
    "add.u32 t, da, 1408; mov.b32 u, %84+2566;\n"
    "mov.b64 dA, {t, ha}; mov.b64 dB, {u, hb};\n"
    "wgmma.mma_async.sync.aligned.m64n160k16.f32.bf16.bf16 {%0,%1,%2,%3,%4,%5,%6,%7,%8,%9,%10,%11,%12,%13,%14,%15,%16,%17,%18,%19,%20,%21,%22,%23,%24,%25,%26,%27,%28,%29,%30,%31,%32,%33,%34,%35,%36,%37,%38,%39,%40,%41,%42,%43,%44,%45,%46,%47,%48,%49,%50,%51,%52,%53,%54,%55,%56,%57,%58,%59,%60,%61,%62,%63,%64,%65,%66,%67,%68,%69,%70,%71,%72,%73,%74,%75,%76,%77,%78,%79}, dA, dB, pt, 1, 1, 0, 0;\n"
    "wgmma.commit_group.sync.aligned;\n"
    "W3: mbarrier.try_wait.parity.shared::cta.b64 pw, [fb+24], ph, 100000;\n"
    "@!pw bra W3;\n"
    "wgmma.fence.sync.aligned;\n"
    "add.u32 t, da, 1536; mov.b32 u, %84+3840;\n"
    "mov.b64 dA, {t, ha}; mov.b64 dB, {u, hb};\n"
    "wgmma.mma_async.sync.aligned.m64n160k16.f32.bf16.bf16 {%0,%1,%2,%3,%4,%5,%6,%7,%8,%9,%10,%11,%12,%13,%14,%15,%16,%17,%18,%19,%20,%21,%22,%23,%24,%25,%26,%27,%28,%29,%30,%31,%32,%33,%34,%35,%36,%37,%38,%39,%40,%41,%42,%43,%44,%45,%46,%47,%48,%49,%50,%51,%52,%53,%54,%55,%56,%57,%58,%59,%60,%61,%62,%63,%64,%65,%66,%67,%68,%69,%70,%71,%72,%73,%74,%75,%76,%77,%78,%79}, dA, dB, pt, 1, 1, 0, 0;\n"
    "add.u32 t, da, 1664; mov.b32 u, %84+3842;\n"
    "mov.b64 dA, {t, ha}; mov.b64 dB, {u, hb};\n"
    "wgmma.mma_async.sync.aligned.m64n160k16.f32.bf16.bf16 {%0,%1,%2,%3,%4,%5,%6,%7,%8,%9,%10,%11,%12,%13,%14,%15,%16,%17,%18,%19,%20,%21,%22,%23,%24,%25,%26,%27,%28,%29,%30,%31,%32,%33,%34,%35,%36,%37,%38,%39,%40,%41,%42,%43,%44,%45,%46,%47,%48,%49,%50,%51,%52,%53,%54,%55,%56,%57,%58,%59,%60,%61,%62,%63,%64,%65,%66,%67,%68,%69,%70,%71,%72,%73,%74,%75,%76,%77,%78,%79}, dA, dB, pt, 1, 1, 0, 0;\n"
    "wgmma.commit_group.sync.aligned;\n"
    "wgmma.wait_group.sync.aligned 1;\n"
    "@pe mbarrier.arrive.shared::cta.b64 _, [fb+%86+16];\n"
    "add.u32 t, da, 1792; mov.b32 u, %84+3844;\n"
    "mov.b64 dA, {t, ha}; mov.b64 dB, {u, hb};\n"
    "wgmma.mma_async.sync.aligned.m64n160k16.f32.bf16.bf16 {%0,%1,%2,%3,%4,%5,%6,%7,%8,%9,%10,%11,%12,%13,%14,%15,%16,%17,%18,%19,%20,%21,%22,%23,%24,%25,%26,%27,%28,%29,%30,%31,%32,%33,%34,%35,%36,%37,%38,%39,%40,%41,%42,%43,%44,%45,%46,%47,%48,%49,%50,%51,%52,%53,%54,%55,%56,%57,%58,%59,%60,%61,%62,%63,%64,%65,%66,%67,%68,%69,%70,%71,%72,%73,%74,%75,%76,%77,%78,%79}, dA, dB, pt, 1, 1, 0, 0;\n"
    "add.u32 t, da, 1920; mov.b32 u, %84+3846;\n"
    "mov.b64 dA, {t, ha}; mov.b64 dB, {u, hb};\n"
    "wgmma.mma_async.sync.aligned.m64n160k16.f32.bf16.bf16 {%0,%1,%2,%3,%4,%5,%6,%7,%8,%9,%10,%11,%12,%13,%14,%15,%16,%17,%18,%19,%20,%21,%22,%23,%24,%25,%26,%27,%28,%29,%30,%31,%32,%33,%34,%35,%36,%37,%38,%39,%40,%41,%42,%43,%44,%45,%46,%47,%48,%49,%50,%51,%52,%53,%54,%55,%56,%57,%58,%59,%60,%61,%62,%63,%64,%65,%66,%67,%68,%69,%70,%71,%72,%73,%74,%75,%76,%77,%78,%79}, dA, dB, pt, 1, 1, 0, 0;\n"
    "wgmma.commit_group.sync.aligned;\n"
    "W4: mbarrier.try_wait.parity.shared::cta.b64 pw, [fb+32], ph, 100000;\n"
    "@!pw bra W4;\n"
    "wgmma.fence.sync.aligned;\n"
    "add.u32 t, da, 2048; mov.b32 u, %84+5120;\n"
    "mov.b64 dA, {t, ha}; mov.b64 dB, {u, hb};\n"
    "wgmma.mma_async.sync.aligned.m64n160k16.f32.bf16.bf16 {%0,%1,%2,%3,%4,%5,%6,%7,%8,%9,%10,%11,%12,%13,%14,%15,%16,%17,%18,%19,%20,%21,%22,%23,%24,%25,%26,%27,%28,%29,%30,%31,%32,%33,%34,%35,%36,%37,%38,%39,%40,%41,%42,%43,%44,%45,%46,%47,%48,%49,%50,%51,%52,%53,%54,%55,%56,%57,%58,%59,%60,%61,%62,%63,%64,%65,%66,%67,%68,%69,%70,%71,%72,%73,%74,%75,%76,%77,%78,%79}, dA, dB, pt, 1, 1, 0, 0;\n"
    "add.u32 t, da, 2176; mov.b32 u, %84+5122;\n"
    "mov.b64 dA, {t, ha}; mov.b64 dB, {u, hb};\n"
    "wgmma.mma_async.sync.aligned.m64n160k16.f32.bf16.bf16 {%0,%1,%2,%3,%4,%5,%6,%7,%8,%9,%10,%11,%12,%13,%14,%15,%16,%17,%18,%19,%20,%21,%22,%23,%24,%25,%26,%27,%28,%29,%30,%31,%32,%33,%34,%35,%36,%37,%38,%39,%40,%41,%42,%43,%44,%45,%46,%47,%48,%49,%50,%51,%52,%53,%54,%55,%56,%57,%58,%59,%60,%61,%62,%63,%64,%65,%66,%67,%68,%69,%70,%71,%72,%73,%74,%75,%76,%77,%78,%79}, dA, dB, pt, 1, 1, 0, 0;\n"
    "wgmma.commit_group.sync.aligned;\n"
    "wgmma.wait_group.sync.aligned 1;\n"
    "@pe mbarrier.arrive.shared::cta.b64 _, [fb+%86+24];\n"
    "setp.eq.b32 pw, n, 1; selp.b32 t, %90, %87, pw;\n"
    "@pe mbarrier.arrive.shared::cta.b64 _, [t];\n"
    "add.u32 t, da, 2304; mov.b32 u, %84+5124;\n"
    "mov.b64 dA, {t, ha}; mov.b64 dB, {u, hb};\n"
    "wgmma.mma_async.sync.aligned.m64n160k16.f32.bf16.bf16 {%0,%1,%2,%3,%4,%5,%6,%7,%8,%9,%10,%11,%12,%13,%14,%15,%16,%17,%18,%19,%20,%21,%22,%23,%24,%25,%26,%27,%28,%29,%30,%31,%32,%33,%34,%35,%36,%37,%38,%39,%40,%41,%42,%43,%44,%45,%46,%47,%48,%49,%50,%51,%52,%53,%54,%55,%56,%57,%58,%59,%60,%61,%62,%63,%64,%65,%66,%67,%68,%69,%70,%71,%72,%73,%74,%75,%76,%77,%78,%79}, dA, dB, pt, 1, 1, 0, 0;\n"
    "sub.u32 n, n, 1; setp.ne.b32 pl, n, 0; setp.eq.b32 ps, 0, 0; xor.b32 ph, ph, 1; add.u32 pa, fb, %86+32; mov.b32 xw, %91;\n"
    "add.u32 t, da, 2432; mov.b32 u, %84+5126;\n"
    "mov.b64 dA, {t, ha}; mov.b64 dB, {u, hb};\n"
    "wgmma.mma_async.sync.aligned.m64n160k16.f32.bf16.bf16 {%0,%1,%2,%3,%4,%5,%6,%7,%8,%9,%10,%11,%12,%13,%14,%15,%16,%17,%18,%19,%20,%21,%22,%23,%24,%25,%26,%27,%28,%29,%30,%31,%32,%33,%34,%35,%36,%37,%38,%39,%40,%41,%42,%43,%44,%45,%46,%47,%48,%49,%50,%51,%52,%53,%54,%55,%56,%57,%58,%59,%60,%61,%62,%63,%64,%65,%66,%67,%68,%69,%70,%71,%72,%73,%74,%75,%76,%77,%78,%79}, dA, dB, pt, 1, 1, 0, 0;\n"
    "wgmma.commit_group.sync.aligned;\n"
    "add.u32 da, da, 2560;\n"
    "@pl bra LOOP; }\n"
    : "+f"(d[0]),"+f"(d[1]),"+f"(d[2]),"+f"(d[3]),"+f"(d[4]),"+f"(d[5]),"+f"(d[6]),"+f"(d[7]),"+f"(d[8]),"+f"(d[9]),"+f"(d[10]),"+f"(d[11]),"+f"(d[12]),"+f"(d[13]),"+f"(d[14]),"+f"(d[15]),"+f"(d[16]),"+f"(d[17]),"+f"(d[18]),"+f"(d[19]),"+f"(d[20]),"+f"(d[21]),"+f"(d[22]),"+f"(d[23]),"+f"(d[24]),"+f"(d[25]),"+f"(d[26]),"+f"(d[27]),"+f"(d[28]),"+f"(d[29]),"+f"(d[30]),"+f"(d[31]),"+f"(d[32]),"+f"(d[33]),"+f"(d[34]),"+f"(d[35]),"+f"(d[36]),"+f"(d[37]),"+f"(d[38]),"+f"(d[39]),"+f"(d[40]),"+f"(d[41]),"+f"(d[42]),"+f"(d[43]),"+f"(d[44]),"+f"(d[45]),"+f"(d[46]),"+f"(d[47]),"+f"(d[48]),"+f"(d[49]),"+f"(d[50]),"+f"(d[51]),"+f"(d[52]),"+f"(d[53]),"+f"(d[54]),"+f"(d[55]),"+f"(d[56]),"+f"(d[57]),"+f"(d[58]),"+f"(d[59]),"+f"(d[60]),"+f"(d[61]),"+f"(d[62]),"+f"(d[63]),"+f"(d[64]),"+f"(d[65]),"+f"(d[66]),"+f"(d[67]),"+f"(d[68]),"+f"(d[69]),"+f"(d[70]),"+f"(d[71]),"+f"(d[72]),"+f"(d[73]),"+f"(d[74]),"+f"(d[75]),"+f"(d[76]),"+f"(d[77]),"+f"(d[78]),"+f"(d[79])
    : "r"(da), "r"(ph), "r"(n), "r"(xw), "n"(desc_lo(A_RING, 16)), "n"(BAR_FULL), "n"(BAR_EMPTY - BAR_FULL),
      "n"(BAR_DUMMY), "n"(kHiSw128), "n"(kHiPlain), "r"(tok), "n"(BAR_P1)
    : "memory");
}
__device__ __forceinline__ void b_mainloop(float* d, float* e, int n, uint32_t own, uint32_t tok) {
  asm volatile(
    "{ .reg .pred pe, pw, pl, ps, pt; .reg .b32 da, db, dv, om, hb, s8, ph, n, pa, t, u; .reg .b64 dA, dB;\n"
    "mov.b32 s8, 0; mov.b32 ph, 0; mov.b32 n, %160; mov.b32 om, %167; mov.b32 pa, %164; mov.b32 hb, %165; mov.b32 dv, %166;\n"
    "mov.u32 t, %%laneid; setp.eq.u32 pe, t, 0; setp.ne.b32 ps, 0, 0; setp.eq.b32 pt, 0, 0;\n"
    "LOOP: add.u32 u, s8, %162;\n"
    "W0: mbarrier.try_wait.parity.shared::cta.b64 pw, [u], ph, 100000;\n"
    "@!pw bra W0;\n"
    "mad.lo.u32 da, s8, 288, %161; add.u32 db, da, 1024; and.b32 t, om, 1; setp.ne.u32 pw, t, 0; shr.u32 om, om, 1; mad.lo.u32 t, s8, 160, dv; selp.b32 db, t, db, pw;\n"
    "wgmma.fence.sync.aligned;\n"
    "add.u32 t, da, 0; add.u32 u, db, 0;\n"
    "mov.b64 dA, {t, hb}; mov.b64 dB, {u, hb};\n"
    "wgmma.mma_async.sync.aligned.m64n160k16.f32.bf16.bf16 {%0,%1,%2,%3,%4,%5,%6,%7,%8,%9,%10,%11,%12,%13,%14,%15,%16,%17,%18,%19,%20,%21,%22,%23,%24,%25,%26,%27,%28,%29,%30,%31,%32,%33,%34,%35,%36,%37,%38,%39,%40,%41,%42,%43,%44,%45,%46,%47,%48,%49,%50,%51,%52,%53,%54,%55,%56,%57,%58,%59,%60,%61,%62,%63,%64,%65,%66,%67,%68,%69,%70,%71,%72,%73,%74,%75,%76,%77,%78,%79}, dA, dB, ps, 1, 1, 0, 0;\n"
    "add.u32 t, da, 512; add.u32 u, db, 0;\n"
    "mov.b64 dA, {t, hb}; mov.b64 dB, {u, hb};\n"
    "wgmma.mma_async.sync.aligned.m64n160k16.f32.bf16.bf16 {%80,%81,%82,%83,%84,%85,%86,%87,%88,%89,%90,%91,%92,%93,%94,%95,%96,%97,%98,%99,%100,%101,%102,%103,%104,%105,%106,%107,%108,%109,%110,%111,%112,%113,%114,%115,%116,%117,%118,%119,%120,%121,%122,%123,%124,%125,%126,%127,%128,%129,%130,%131,%132,%133,%134,%135,%136,%137,%138,%139,%140,%141,%142,%143,%144,%145,%146,%147,%148,%149,%150,%151,%152,%153,%154,%155,%156,%157,%158,%159}, dA, dB, ps, 1, 1, 0, 0;\n"
    "wgmma.commit_group.sync.aligned;\n"
    "wgmma.wait_group.sync.aligned 1;\n"
    "@pe mbarrier.arrive.shared::cta.b64 _, [pa];\n"
    "add.u32 pa, s8, %163;\n"
    "add.u32 t, da, 2; add.u32 u, db, 2;\n"
    "mov.b64 dA, {t, hb}; mov.b64 dB, {u, hb};\n"
    "wgmma.mma_async.sync.aligned.m64n160k16.f32.bf16.bf16 {%0,%1,%2,%3,%4,%5,%6,%7,%8,%9,%10,%11,%12,%13,%14,%15,%16,%17,%18,%19,%20,%21,%22,%23,%24,%25,%26,%27,%28,%29,%30,%31,%32,%33,%34,%35,%36,%37,%38,%39,%40,%41,%42,%43,%44,%45,%46,%47,%48,%49,%50,%51,%52,%53,%54,%55,%56,%57,%58,%59,%60,%61,%62,%63,%64,%65,%66,%67,%68,%69,%70,%71,%72,%73,%74,%75,%76,%77,%78,%79}, dA, dB, pt, 1, 1, 0, 0;\n"
    "add.u32 t, da, 514; add.u32 u, db, 2;\n"
    "mov.b64 dA, {t, hb}; mov.b64 dB, {u, hb};\n"
    "wgmma.mma_async.sync.aligned.m64n160k16.f32.bf16.bf16 {%80,%81,%82,%83,%84,%85,%86,%87,%88,%89,%90,%91,%92,%93,%94,%95,%96,%97,%98,%99,%100,%101,%102,%103,%104,%105,%106,%107,%108,%109,%110,%111,%112,%113,%114,%115,%116,%117,%118,%119,%120,%121,%122,%123,%124,%125,%126,%127,%128,%129,%130,%131,%132,%133,%134,%135,%136,%137,%138,%139,%140,%141,%142,%143,%144,%145,%146,%147,%148,%149,%150,%151,%152,%153,%154,%155,%156,%157,%158,%159}, dA, dB, pt, 1, 1, 0, 0;\n"
    "add.u32 s8, s8, 8; setp.eq.b32 pw, s8, 40; @pw mov.b32 s8, 0; @pw xor.b32 ph, ph, 1; sub.u32 n, n, 1; setp.eq.b32 ps, 0, 0;\n"
    "add.u32 t, da, 4; add.u32 u, db, 4;\n"
    "mov.b64 dA, {t, hb}; mov.b64 dB, {u, hb};\n"
    "wgmma.mma_async.sync.aligned.m64n160k16.f32.bf16.bf16 {%0,%1,%2,%3,%4,%5,%6,%7,%8,%9,%10,%11,%12,%13,%14,%15,%16,%17,%18,%19,%20,%21,%22,%23,%24,%25,%26,%27,%28,%29,%30,%31,%32,%33,%34,%35,%36,%37,%38,%39,%40,%41,%42,%43,%44,%45,%46,%47,%48,%49,%50,%51,%52,%53,%54,%55,%56,%57,%58,%59,%60,%61,%62,%63,%64,%65,%66,%67,%68,%69,%70,%71,%72,%73,%74,%75,%76,%77,%78,%79}, dA, dB, pt, 1, 1, 0, 0;\n"
    "add.u32 t, da, 516; add.u32 u, db, 4;\n"
    "mov.b64 dA, {t, hb}; mov.b64 dB, {u, hb};\n"
    "wgmma.mma_async.sync.aligned.m64n160k16.f32.bf16.bf16 {%80,%81,%82,%83,%84,%85,%86,%87,%88,%89,%90,%91,%92,%93,%94,%95,%96,%97,%98,%99,%100,%101,%102,%103,%104,%105,%106,%107,%108,%109,%110,%111,%112,%113,%114,%115,%116,%117,%118,%119,%120,%121,%122,%123,%124,%125,%126,%127,%128,%129,%130,%131,%132,%133,%134,%135,%136,%137,%138,%139,%140,%141,%142,%143,%144,%145,%146,%147,%148,%149,%150,%151,%152,%153,%154,%155,%156,%157,%158,%159}, dA, dB, pt, 1, 1, 0, 0;\n"
    "setp.eq.b32 pw, n, 0; selp.b32 t, %168, %164, pw;\n"
    "@pe mbarrier.arrive.shared::cta.b64 _, [t];\n"
    "add.u32 t, da, 6; add.u32 u, db, 6;\n"
    "mov.b64 dA, {t, hb}; mov.b64 dB, {u, hb};\n"
    "wgmma.mma_async.sync.aligned.m64n160k16.f32.bf16.bf16 {%0,%1,%2,%3,%4,%5,%6,%7,%8,%9,%10,%11,%12,%13,%14,%15,%16,%17,%18,%19,%20,%21,%22,%23,%24,%25,%26,%27,%28,%29,%30,%31,%32,%33,%34,%35,%36,%37,%38,%39,%40,%41,%42,%43,%44,%45,%46,%47,%48,%49,%50,%51,%52,%53,%54,%55,%56,%57,%58,%59,%60,%61,%62,%63,%64,%65,%66,%67,%68,%69,%70,%71,%72,%73,%74,%75,%76,%77,%78,%79}, dA, dB, pt, 1, 1, 0, 0;\n"
    "add.u32 t, da, 518; add.u32 u, db, 6;\n"
    "mov.b64 dA, {t, hb}; mov.b64 dB, {u, hb};\n"
    "wgmma.mma_async.sync.aligned.m64n160k16.f32.bf16.bf16 {%80,%81,%82,%83,%84,%85,%86,%87,%88,%89,%90,%91,%92,%93,%94,%95,%96,%97,%98,%99,%100,%101,%102,%103,%104,%105,%106,%107,%108,%109,%110,%111,%112,%113,%114,%115,%116,%117,%118,%119,%120,%121,%122,%123,%124,%125,%126,%127,%128,%129,%130,%131,%132,%133,%134,%135,%136,%137,%138,%139,%140,%141,%142,%143,%144,%145,%146,%147,%148,%149,%150,%151,%152,%153,%154,%155,%156,%157,%158,%159}, dA, dB, pt, 1, 1, 0, 0;\n"
    "wgmma.commit_group.sync.aligned;\n"
    "setp.ne.b32 pl, n, 0;\n"
    "@pl bra LOOP; }\n"
    : "+f"(d[0]),"+f"(d[1]),"+f"(d[2]),"+f"(d[3]),"+f"(d[4]),"+f"(d[5]),"+f"(d[6]),"+f"(d[7]),"+f"(d[8]),"+f"(d[9]),"+f"(d[10]),"+f"(d[11]),"+f"(d[12]),"+f"(d[13]),"+f"(d[14]),"+f"(d[15]),"+f"(d[16]),"+f"(d[17]),"+f"(d[18]),"+f"(d[19]),"+f"(d[20]),"+f"(d[21]),"+f"(d[22]),"+f"(d[23]),"+f"(d[24]),"+f"(d[25]),"+f"(d[26]),"+f"(d[27]),"+f"(d[28]),"+f"(d[29]),"+f"(d[30]),"+f"(d[31]),"+f"(d[32]),"+f"(d[33]),"+f"(d[34]),"+f"(d[35]),"+f"(d[36]),"+f"(d[37]),"+f"(d[38]),"+f"(d[39]),"+f"(d[40]),"+f"(d[41]),"+f"(d[42]),"+f"(d[43]),"+f"(d[44]),"+f"(d[45]),"+f"(d[46]),"+f"(d[47]),"+f"(d[48]),"+f"(d[49]),"+f"(d[50]),"+f"(d[51]),"+f"(d[52]),"+f"(d[53]),"+f"(d[54]),"+f"(d[55]),"+f"(d[56]),"+f"(d[57]),"+f"(d[58]),"+f"(d[59]),"+f"(d[60]),"+f"(d[61]),"+f"(d[62]),"+f"(d[63]),"+f"(d[64]),"+f"(d[65]),"+f"(d[66]),"+f"(d[67]),"+f"(d[68]),"+f"(d[69]),"+f"(d[70]),"+f"(d[71]),"+f"(d[72]),"+f"(d[73]),"+f"(d[74]),"+f"(d[75]),"+f"(d[76]),"+f"(d[77]),"+f"(d[78]),"+f"(d[79]),"+f"(e[0]),"+f"(e[1]),"+f"(e[2]),"+f"(e[3]),"+f"(e[4]),"+f"(e[5]),"+f"(e[6]),"+f"(e[7]),"+f"(e[8]),"+f"(e[9]),"+f"(e[10]),"+f"(e[11]),"+f"(e[12]),"+f"(e[13]),"+f"(e[14]),"+f"(e[15]),"+f"(e[16]),"+f"(e[17]),"+f"(e[18]),"+f"(e[19]),"+f"(e[20]),"+f"(e[21]),"+f"(e[22]),"+f"(e[23]),"+f"(e[24]),"+f"(e[25]),"+f"(e[26]),"+f"(e[27]),"+f"(e[28]),"+f"(e[29]),"+f"(e[30]),"+f"(e[31]),"+f"(e[32]),"+f"(e[33]),"+f"(e[34]),"+f"(e[35]),"+f"(e[36]),"+f"(e[37]),"+f"(e[38]),"+f"(e[39]),"+f"(e[40]),"+f"(e[41]),"+f"(e[42]),"+f"(e[43]),"+f"(e[44]),"+f"(e[45]),"+f"(e[46]),"+f"(e[47]),"+f"(e[48]),"+f"(e[49]),"+f"(e[50]),"+f"(e[51]),"+f"(e[52]),"+f"(e[53]),"+f"(e[54]),"+f"(e[55]),"+f"(e[56]),"+f"(e[57]),"+f"(e[58]),"+f"(e[59]),"+f"(e[60]),"+f"(e[61]),"+f"(e[62]),"+f"(e[63]),"+f"(e[64]),"+f"(e[65]),"+f"(e[66]),"+f"(e[67]),"+f"(e[68]),"+f"(e[69]),"+f"(e[70]),"+f"(e[71]),"+f"(e[72]),"+f"(e[73]),"+f"(e[74]),"+f"(e[75]),"+f"(e[76]),"+f"(e[77]),"+f"(e[78]),"+f"(e[79])
    : "r"(n), "n"(desc_lo(B_RING, 16)), "n"(BAR_FULL), "n"(BAR_EMPTY), "n"(BAR_DUMMY), "n"(kHiSw128), "n"(desc_lo(B_STG, 16)),
      "r"(own), "r"(tok)
    : "memory");
}

__device__ __forceinline__ void mbar_init(uint32_t bar, uint32_t cnt) { asm volatile("mbarrier.init.shared::cta.b64 [%0], %1;" ::"r"(bar), "r"(cnt) : "memory"); }
__device__ __forceinline__ void mbar_expect(uint32_t bar, uint32_t bytes) { asm volatile("{ .reg .pred e; elect.sync _|e, 0xffffffff;\n@e mbarrier.arrive.expect_tx.shared::cta.b64 _, [%0], %1; }" ::"r"(bar), "r"(bytes) : "memory"); }
__device__ __forceinline__ void mbar_arrive1(uint32_t bar) { asm volatile("{ .reg .pred e; elect.sync _|e, 0xffffffff;\n@e mbarrier.arrive.shared::cta.b64 _, [%0]; }" ::"r"(bar) : "memory"); }
__device__ __forceinline__ void mbar_arrive(uint32_t bar) { asm volatile("mbarrier.arrive.shared::cta.b64 _, [%0];" ::"r"(bar) : "memory"); }
__device__ __forceinline__ void mbar_wait(uint32_t bar, uint32_t parity) {
  asm volatile("{ .reg .pred p;\nLAB_WAIT: mbarrier.try_wait.parity.shared::cta.b64 p, [%0], %1, 100000;\n@!p bra LAB_WAIT; }" ::"r"(bar), "r"(parity) : "memory");
}
__device__ __forceinline__ void mbar_poll(uint32_t bar) {
  asm volatile("{ .reg .pred p;\nLAB_WAIT: mbarrier.test_wait.parity.shared::cta.b64 p, [%0], 0;\n@!p bra LAB_WAIT; }" ::"r"(bar) : "memory");
}
__device__ __forceinline__ void wg_bar(int wg) { asm volatile("bar.sync %0, 128;" ::"r"(wg + 1) : "memory"); }
__device__ __forceinline__ void fence_async_smem() { asm volatile("fence.proxy.async.shared::cta;" ::: "memory"); }

__device__ __forceinline__ void tma2d(uint32_t dst, const CUtensorMap* m, int c0, int c1, uint32_t bar) {
  asm volatile("{ .reg .pred e; elect.sync _|e, 0xffffffff;\n@e cp.async.bulk.tensor.2d.shared::cluster.global.mbarrier::complete_tx::bytes [%0], [%1, {%3,%4}], [%2]; }" ::"r"(dst), "l"(m), "r"(bar), "r"(c0), "r"(c1) : "memory");
}
__device__ __forceinline__ void tma3d(uint32_t dst, const CUtensorMap* m, int c0, int c1, int c2, uint32_t bar) {
  asm volatile("{ .reg .pred e; elect.sync _|e, 0xffffffff;\n@e cp.async.bulk.tensor.3d.shared::cluster.global.mbarrier::complete_tx::bytes [%0], [%1, {%3,%4,%5}], [%2]; }" ::"r"(dst), "l"(m), "r"(bar), "r"(c0), "r"(c1), "r"(c2) : "memory");
}
__device__ __forceinline__ void tma5d(uint32_t dst, const CUtensorMap* m, int c0, int c1, int c2, int c3, int c4, uint32_t bar) {
  asm volatile("{ .reg .pred e; elect.sync _|e, 0xffffffff;\n@e cp.async.bulk.tensor.5d.shared::cluster.global.mbarrier::complete_tx::bytes [%0], [%1, {%3,%4,%5,%6,%7}], [%2]; }" ::"r"(dst), "l"(m), "r"(bar), "r"(c0), "r"(c1), "r"(c2), "r"(c3), "r"(c4) : "memory");
}
__device__ __forceinline__ void prefetch3d(const CUtensorMap* m, int c0, int c1, int c2) {
  asm volatile("{ .reg .pred e; elect.sync _|e, 0xffffffff;\n@e cp.async.bulk.prefetch.tensor.3d.L2.global [%0, {%1,%2,%3}]; }" ::"l"(m), "r"(c0), "r"(c1), "r"(c2) : "memory");
}
__device__ __forceinline__ void prefetch_l2(const void* p, uint32_t bytes) {
  asm volatile("{ .reg .pred e; elect.sync _|e, 0xffffffff;\n@e cp.async.bulk.prefetch.L2.global [%0], %1; }" ::"l"(p), "r"(bytes) : "memory");
}
__device__ __forceinline__ void bulk_load(uint32_t dst, const void* src, uint32_t bytes, uint32_t bar) {
  asm volatile("{ .reg .pred e; elect.sync _|e, 0xffffffff;\n@e cp.async.bulk.shared::cluster.global.mbarrier::complete_tx::bytes [%0], [%1], %2, [%3]; }" ::"r"(dst), "l"(src), "r"(bytes), "r"(bar) : "memory");
}
__device__ __forceinline__ void bulk_store(void* dst, uint32_t src, uint32_t bytes) {
  asm volatile("{ .reg .pred e; elect.sync _|e, 0xffffffff;\n@e cp.async.bulk.global.shared::cta.bulk_group [%0], [%1], %2; }" ::"l"(dst), "r"(src), "r"(bytes) : "memory");
}
__device__ __forceinline__ void bulk_reduce(void* dst, uint32_t src, uint32_t bytes) {
  asm volatile("{ .reg .pred e; elect.sync _|e, 0xffffffff;\n@e cp.reduce.async.bulk.global.shared::cta.bulk_group.add.noftz.bf16 [%0], [%1], %2; }" ::"l"(dst), "r"(src), "r"(bytes) : "memory");
}
__device__ __forceinline__ void bulk_wait() { asm volatile("cp.async.bulk.commit_group;\ncp.async.bulk.wait_group 0;" ::: "memory"); }
__device__ __forceinline__ unsigned load_epoch_raw(const Params& P) {
  unsigned v;
  asm volatile("ld.global.cg.u32 %0, [%1];" : "=r"(v) : "l"(P.s->ep + blockIdx.x * 32) : "memory");
  return v;
}
__device__ __forceinline__ unsigned load_epoch(const Params& P) { return __shfl_sync(~0u, load_epoch_raw(P) + 1, 0); }
__device__ __forceinline__ void pace(uint32_t t0, uint32_t dt) { while ((uint32_t)clock() - t0 < dt) {} }
__device__ __forceinline__ void paced_store(unsigned char* dst, uint32_t src, uint32_t piece, int n, uint32_t dt) {
#pragma unroll 1
  for (int i = 0; i < n; i++) {
    if (i) __nanosleep(dt);
    bulk_store(dst + i * piece, src + i * piece, piece);
  }
}
__device__ __forceinline__ void cnt_add(const Params& P, int idx) {
  asm volatile("{ .reg .pred e; elect.sync _|e, 0xffffffff;\n@e red.release.gpu.global.add.u32 [%0], 1; }" ::"l"(P.s->cnt + idx) : "memory");
}
__device__ __forceinline__ void cnt_wait(const Params& P, int idx, unsigned target) {
  asm volatile("{ .reg .pred p; .reg .s32 v;\nLAB_POLL: ld.relaxed.gpu.global.s32 v, [%0];\nsub.s32 v, v, %1; setp.lt.s32 p, v, 0;\n@p bra LAB_POLL; }" ::"l"(P.s->cnt + idx), "r"(target) : "memory");
}

__device__ __forceinline__ uint32_t line_wait(const Params& P, int idx, unsigned target, uint32_t need, uint32_t ns) {
  uint32_t have;
  do {
    if (ns) __nanosleep(ns);
    int v;
    asm volatile("ld.relaxed.gpu.global.s32 %0, [%1];" : "=r"(v) : "l"(P.s->cnt + idx + (threadIdx.x & 31)) : "memory");
    have = __ballot_sync(~0u, v - (int)target >= 0);
  } while ((have & need) != need);
  return have;
}

__device__ __forceinline__ uint32_t pack2(float lo, float hi) {
  uint32_t r;
  asm("cvt.rn.bf16x2.f32 %0, %1, %2;" : "=r"(r) : "f"(hi), "f"(lo));
  return r;
}
__device__ __forceinline__ float ex2(float x) { float r; asm("ex2.approx.ftz.f32 %0, %1;" : "=f"(r) : "f"(x)); return r; }
__device__ __forceinline__ float rcp(float x) { float r; asm("rcp.approx.ftz.f32 %0, %1;" : "=f"(r) : "f"(x)); return r; }
__device__ __forceinline__ void sts128(uint32_t a, uint32_t x, uint32_t y, uint32_t z, uint32_t w) {
  asm volatile("st.shared.v4.b32 [%0], {%1,%2,%3,%4};" ::"r"(a), "r"(x), "r"(y), "r"(z), "r"(w) : "memory");
}
__device__ __forceinline__ void lds128(uint32_t a, uint32_t* r) {
  asm volatile("ld.shared.v4.b32 {%0,%1,%2,%3}, [%4];" : "=r"(r[0]), "=r"(r[1]), "=r"(r[2]), "=r"(r[3]) : "r"(a) : "memory");
}
__device__ __forceinline__ void ldsm4(uint32_t a, uint32_t* r) {
  asm volatile("ldmatrix.sync.aligned.m8n8.x4.shared.b16 {%0,%1,%2,%3}, [%4];" : "=r"(r[0]), "=r"(r[1]), "=r"(r[2]), "=r"(r[3]) : "r"(a) : "memory");
}
__device__ __forceinline__ void ldsm4t(uint32_t a, uint32_t* r) {
  asm volatile("ldmatrix.sync.aligned.m8n8.x4.trans.shared.b16 {%0,%1,%2,%3}, [%4];" : "=r"(r[0]), "=r"(r[1]), "=r"(r[2]), "=r"(r[3]) : "r"(a) : "memory");
}
__device__ __forceinline__ void stsm4(uint32_t a, uint32_t x, uint32_t y, uint32_t z, uint32_t w) {
  asm volatile("stmatrix.sync.aligned.m8n8.x4.shared.b16 [%0], {%1,%2,%3,%4};" ::"r"(a), "r"(x), "r"(y), "r"(z), "r"(w) : "memory");
}
__device__ __forceinline__ void stsm2(uint32_t a, uint32_t x, uint32_t y) {
  asm volatile("stmatrix.sync.aligned.m8n8.x2.shared.b16 [%0], {%1,%2};" ::"r"(a), "r"(x), "r"(y) : "memory");
}
__device__ __forceinline__ void stsm4t(uint32_t a, uint32_t x, uint32_t y, uint32_t z, uint32_t w) {
  asm volatile("stmatrix.sync.aligned.m8n8.x4.trans.shared.b16 [%0], {%1,%2,%3,%4};" ::"r"(a), "r"(x), "r"(y), "r"(z), "r"(w) : "memory");
}
__device__ __forceinline__ void mma16(float* d, uint32_t a0, uint32_t a1, uint32_t a2, uint32_t a3, uint32_t b0, uint32_t b1) {
  asm("mma.sync.aligned.m16n8k16.row.col.f32.bf16.bf16.f32 {%0,%1,%2,%3},{%4,%5,%6,%7},{%8,%9},{%0,%1,%2,%3};"
      : "+f"(d[0]), "+f"(d[1]), "+f"(d[2]), "+f"(d[3]) : "r"(a0), "r"(a1), "r"(a2), "r"(a3), "r"(b0), "r"(b1));
}
__device__ __forceinline__ void mma8(float* d, uint32_t a0, uint32_t a1, uint32_t b0) {
  asm("mma.sync.aligned.m16n8k8.row.col.f32.bf16.bf16.f32 {%0,%1,%2,%3},{%4,%5},{%6},{%0,%1,%2,%3};"
      : "+f"(d[0]), "+f"(d[1]), "+f"(d[2]), "+f"(d[3]) : "r"(a0), "r"(a1), "r"(b0));
}
__device__ __forceinline__ float bf_lo(uint32_t v) { return __uint_as_float(v << 16); }
__device__ __forceinline__ float bf_hi(uint32_t v) { return __uint_as_float(v & 0xffff0000u); }
__device__ __forceinline__ float ldbf(const __nv_bfloat16* p) { return __bfloat162float(__ldg(p)); }

#define H_ENDS 4, 8, 12, 16
__host__ __device__ constexpr int h_end(int c) { constexpr int e[5] = {H_ENDS, 20}; return e[c]; }
#define XFAST 0
#define H_GATE 1
#define KPAUSE 0
#define RED_NS 40
#define J1 3
constexpr uint32_t A_KV0 = KV_R == 2 ? A_X : A_X + kBlob, A_KV1 = A_X + 81920 - KV_R * kKvBytes;
#define H_ALL 0
#define PR_XA 2
#define PR_XB 2
#define PR_B 2
#define SM_UNROLL
#define WO_T 6500
#define A_PRE 3
#define O_SWAP 0
#define TA0 0
#define TA1 0
#define TA2 0
#define TAV 0
#define TB0 0
#define H_C 5
#define V_LAG 1
#define RED_B 2048
#define KV_PF 0
#define NUM_PF 0
#define O_S1 0
#define XLA 1
#define A_PF 3
#define P_PACE0 4000
#define P_PACE 500
#define H_N 20
#define H_PACE 150
#define O_N 1
#define O_PACE 200
#define RED_PACE1 RED_PACE
#define O_S2 5
#define B_SPLIT 0
#define B_HOLD 0
#define SM_PK
#define MAP 0
#define NUM_U 4
#define RED_N 20
#define RED_PACE 220
#define A_SLEEP 0
#define B_SLEEP 100
#define A_PACE 300
#define B_PACE 600
#define B_PACE0 600
__device__ __forceinline__ int tile_pos(int job) {
  const int grp = job / 10, kb = job - 10 * grp, w0 = grp & 1;
  return (grp & 2) * 30 + kb + (grp < 8 ? (grp >> 2) * 20 + (w0 ? 0 : 10) : w0 ? 45 : kb < 5 ? 40 : 50);
}

__device__ __forceinline__ int tile_counter(int job) {
  const int grp = job / 10;
  return C_W + (grp & 2) * 16 + (grp >> 2) * 2 + (~grp & 1);
}

__device__ __forceinline__ void a_producer(const Params& P, int rb, int half, long long t_start) {
  const uint32_t c0 = clock();
#pragma unroll 1
  for (int n = A_PRE; n < 5; n++) {
    pace(c0, (n - A_PRE) * A_PACE);
    if (n >= 2) {
      const int kb = n - 1;
      mbar_expect(BAR_X + 8 * kb, 8192);
      tma2d(A_X + kb * 8192, &P.xa, kb * 64, rb * 64, BAR_X + 8 * kb);
    }
    ST(n);
    mbar_expect(BAR_FULL + 8 * n, kBlob);
    tma3d(A_RING + n * kBlob, &P.wv, 0, n * 32, 20 + 5 * half, BAR_FULL + 8 * n);
    if (n == A_PF && rb >= 5 && rb < 20) prefetch3d(&P.wv, 0, rb * 32, 20 + 5 * half);
  }
#pragma unroll 1
  for (int r = 1; r < 4; r++) {
#pragma unroll
    for (int s = 0; s < 5; s++) {
      mbar_wait(BAR_EMPTY + 8 * s, (r & 1) ^ 1);
      ST(5 * r + s);
      mbar_expect(BAR_FULL + 8 * s, kBlob);
      tma3d(A_RING + s * kBlob, &P.wv, 0, (5 * r + s) * 32, 20 + 5 * half, BAR_FULL + 8 * s);
      if (XFAST ? (r == 1 || (r == 2 && s == 0)) : (!(s & 1) && r < 3)) {
        const int kb = XFAST ? 5 * r - 1 + s : 3 * r + 1 + (s >> 1);
        mbar_expect(BAR_X + 8 * kb, 8192);
        tma2d(A_X + kb * 8192, &P.xa, kb * 64, rb * 64, BAR_X + 8 * kb);
      }
    }
  }
  TS1(40);
  const unsigned char* src = P.s->w + (size_t)half * 60 * kBlob;
#pragma unroll 1
  for (int r = 0; r < 12; r++, src += 5 * kBlob) {
    mbar_wait(BAR_WA + 8 * min(r >> 1, 4), 0);
    if (r == 0) TS1(41);
    const uint32_t bytes = r < 8 ? kFold : kBlob;
#pragma unroll
    for (int s = 0; s < 5; s++) {
      mbar_wait(BAR_EMPTY + 8 * s, (r & 1) ^ 1);
      ST(20 + 5 * r + s);
      mbar_expect(BAR_FULL + 8 * s, bytes);
      bulk_load(A_RING + s * kBlob, src + s * kBlob, bytes, BAR_FULL + 8 * s);
      if (s == (KV_R == 2 ? 3 : 4)) mbar_arrive1(r == 7 ? BAR_KV0 : BAR_DUMMY);
    }
  }
}

__device__ __forceinline__ void a_poller(const Params& P, int half, unsigned ep) {
  uint32_t have = 0;
#pragma unroll 1
  for (int i = 0; i < 5; i++) {
    const uint32_t need = i < 4 ? 1 << i : 48;
    if ((have & need) != need) have = line_wait(P, C_W + half * 32, ep * 10, need, i < 2 ? 0 : 400);
    mbar_arrive1(BAR_WA + 8 * i);
  }
}

__device__ __forceinline__ void a_helper(const Params& P, int rb, int half, unsigned ep, long long t_start) {
#pragma unroll 1
  for (int ty = 0; ty < 2; ty++) {
    const int hg = 2 * half + (ty ^ 1);
    mbar_wait(BAR_RED + 8 * ty, 0);
    const uint32_t c0 = clock();
    constexpr int NP = kKvBytes / RED_B;
#pragma unroll 1
    for (int i = 0; i < NP; i++) {
      const int j = (i + rb / KV_R) & (NP - 1);
      if (RED_NS == 0) pace(c0, i * (ty ? RED_PACE1 : RED_PACE));
      else if (i) __nanosleep(RED_NS);
      bulk_reduce(P.s->kv + (hg * KV_R + rb % KV_R) * kKvBytes + j * RED_B, A_PHI + kHalf + j * RED_B + (j / (NP / 4)) * (kPair - 4096), RED_B);
    }
    asm volatile("cp.async.bulk.commit_group;\ncp.async.bulk.wait_group.read 0;" ::: "memory");
    mbar_arrive1(ty ? BAR_STG1 : BAR_STG);
    TS1(50 + 3 * ty);
    bulk_wait();
    cnt_add(P, C_KV + hg * 32);
    TS1(52 + 3 * ty);
  }
  mbar_expect(BAR_KVR + 8, KV_R * kKvBytes);
  cnt_wait(P, C_KV + 2 * half * 32, ep * 32);
  TS1(43);
  mbar_wait(BAR_QD, 0);
  bulk_load(A_KV1, P.s->kv + 2 * half * KV_R * kKvBytes, KV_R * kKvBytes, BAR_KVR + 8);
}

__device__ __forceinline__ void a_exchange(const Params& P, int rb, int half, unsigned ep, long long t_start) {
  mbar_expect(BAR_KVR, KV_R * kKvBytes);
  mbar_wait(BAR_RED + 8, 0);
  cnt_wait(P, C_KV + (2 * half + 1) * 32, ep * 32);
  TS1(42);
  mbar_wait(BAR_KV0, 0);
  bulk_load(A_KV0, P.s->kv + (2 * half + 1) * KV_R * kKvBytes, KV_R * kKvBytes, BAR_KVR);
  mbar_wait(BAR_QD, 0);
}

__device__ __forceinline__ void a_swap(const Params& P, int rb, int half, int ty, unsigned ep, long long t_start) {
  const int me = rb * 4 + 2 * half + ty;
  const uint32_t reg = A_X + ty * kBlob;
  mbar_expect(BAR_P + 24 * ty, kBlob);
  mbar_wait(BAR_O + 8 * ty, 0);
  paced_store(P.s->ox + (size_t)me * kBlob, reg, kBlob / O_N, O_N, O_PACE);
  bulk_wait();
  TS1(47 + 2 * ty);
  cnt_add(P, C_O + me * 32);
  TS1(51 + 3 * ty);
  cnt_wait(P, C_O + (me ^ 2) * 32, ep);
  if (KV_R == 2) mbar_wait(BAR_O + 8, 0);
  bulk_load(reg + 2 * kBlob, P.s->ox + (size_t)(me ^ 2) * kBlob, kBlob, BAR_P + 24 * ty);
  TS1(44 + ty);
}

template <int WG>
__device__ __forceinline__ void a_vgemm(float* v, int lane, long long t_start) {
#pragma unroll 1
  for (int n = 0; n < 20; n++) {
    const int s = n % A_NS;
    mbar_wait(BAR_X + 8 * (n >> 1), 0);
    mbar_wait(BAR_FULL + 8 * s, (n / A_NS) & 1);
    if (n == 0) TS(0 + 16 * WG);
    const uint32_t da = desc_lo(A_X, 16) + (n >> 1) * 512 + (n & 1) * 4;
    const uint32_t db = desc_lo(A_RING, 4096) + s * (kBlob >> 4) + (WG ? 0 : 768);
    wg_fence();
    if (WG == 0) {
      wgmma_n128<1>(v, mkdesc(da, kHiSw128), mkdesc(db, kHiSw128), n);
      wgmma_n128<1>(v, mkdesc(da + 2, kHiSw128), mkdesc(db + 128, kHiSw128), 1);
    } else {
      wgmma_n192<1>(v, mkdesc(da, kHiSw128), mkdesc(db, kHiSw128), n);
      wgmma_n192<1>(v, mkdesc(da + 2, kHiSw128), mkdesc(db + 128, kHiSw128), 1);
    }
    wg_commit();
    wg_wait<1>();
    if (n) mbar_arrive1(BAR_EMPTY + 8 * (s ? s - 1 : A_NS - 1));
  }
  wg_wait<0>();
}

constexpr float kL = 1.4426950408889634f;
__device__ __forceinline__ void softmax_stats(const float* p, float& mx, float& mn) {
  int x[2];
  unsigned n[2];
#pragma unroll
  for (int i = 0; i < 2; i++) {
    const float* a = p + 36 * i;
    x[i] = __vimax3_s32(__float_as_int(a[0]), __float_as_int(a[4]), __float_as_int(a[8]));
    n[i] = __vimax3_u32(__float_as_uint(a[0]), __float_as_uint(a[4]), __float_as_uint(a[8]));
#pragma unroll
    for (int j = 3; j < 9; j += 2) {
      x[i] = __vimax3_s32(x[i], __float_as_int(a[4 * j]), __float_as_int(a[4 * j + 4]));
      n[i] = __vimax3_u32(n[i], __float_as_uint(a[4 * j]), __float_as_uint(a[4 * j + 4]));
    }
  }
  mx = -kL * __int_as_float(__vimax3_s32_relu(x[0], x[1], __float_as_int(p[72])));
  mn = kL * fminf(__uint_as_float(__vimax3_u32(n[0], n[1], __float_as_uint(p[72]))), 0.f);
}
__device__ __forceinline__ void softmax_group(const float* p, float mx, float mn, uint32_t a) {
  float t[40];
  t[0] = ex2(mx);
  t[20] = ex2(mn);
#pragma unroll
  for (int j = 0; j < 19; j++) t[1 + j] = ex2(fmaf(p[4 * j], kL, mx));
#pragma unroll
  for (int j = 0; j < 19; j++) t[21 + j] = ex2(fmaf(p[4 * j], -kL, mn));
  float s[4];
#pragma unroll
  for (int i = 0; i < 4; i++) s[i] = t[10 * i] + t[10 * i + 1];
#pragma unroll
  for (int j = 2; j < 10; j++)
#pragma unroll
    for (int i = 0; i < 4; i++) s[i] += t[10 * i + j];
  const float rp = rcp(s[0] + s[1]), rn = rcp(s[2] + s[3]);
  uint32_t k[20];
  const uint32_t p2 = pack2(rp, rp), n2 = pack2(rn, rn);
#pragma unroll
  for (int j = 0; j < 20; j++) asm("mul.rn.bf16x2 %0, %1, %2;" : "=r"(k[j]) : "r"(pack2(t[2 * j], t[2 * j + 1])), "r"(j < 10 ? p2 : n2));
#pragma unroll
  for (int c = 0; c < 5; c++) sts128(a + c * 512, k[4 * c], k[4 * c + 1], k[4 * c + 2], k[4 * c + 3]);
}

__device__ __forceinline__ void a_consumer(const Params& P, int rb, int half, int wg, uint32_t c0, long long t_start) {
  const int tid = threadIdx.x & 127, w = tid >> 5, lane = tid & 31, gi = lane >> 2, q = lane & 3;
  const int hg = 2 * half + (wg ^ 1);
  uint32_t hold[48];
  if (tid == 0) sts128(A_ONES, 0x3F803F80u, 0x3F803F80u, 0x3F803F80u, 0x3F803F80u);
  {
    float v[96];
    reg_fence<96>(v);
    if (TAV) pace(c0, TAV);
    if (wg == 0) a_vgemm<0>(v, lane, t_start);
    else a_vgemm<1>(v, lane, t_start);
    reg_fence<96>(v);
    mbar_arrive1(BAR_EMPTY + 32);
    TS(1 + 16 * wg);
    const uint32_t vst = A_PHI + (wg ? 0 : 24576) + (lane >> 4) * 1024 + (16 * w + (lane & 15)) * 16;
#pragma unroll
    for (int cc = 0; cc < 12; cc++) {
      const int c = (cc + 10) % 12;
      if (c < 8 || wg)
        stsm4(vst + c * 2048, pack2(v[8 * c], v[8 * c + 1]), pack2(v[8 * c + 2], v[8 * c + 3]), pack2(v[8 * c + 4], v[8 * c + 5]), pack2(v[8 * c + 6], v[8 * c + 7]));
      if (cc == 1 && wg) {
        asm volatile("bar.arrive 3, 256;" ::: "memory");
        if (V_LAG) asm volatile("bar.sync 4, 256;" ::: "memory");
      }
    }
    if (wg) wg_bar(1);
    else asm volatile("bar.sync 3, 256;" ::: "memory");
    const uint32_t vb = A_PHI + (wg ? 0 : 20480) + w * 5120;
    const uint32_t va = vb + ((lane >> 3) & 1) * 1024 + ((lane & 7) + 8 * (lane >> 4)) * 16;
#pragma unroll
    for (int ks = 0; ks < 4; ks++) {
      ldsm4t(va + ks * 256, hold + 4 * ks);
      ldsm4t(va + 3072 + ks * 256, hold + 16 + 4 * ks);
      ldsm4t((lane & 8) ? A_ONES : va + 2048 + ks * 256, hold + 32 + 4 * ks);
    }
    if (V_LAG && wg == 0) asm volatile("bar.arrive 4, 256;" ::: "memory");
    mbar_arrive1(BAR_V);
  }
  const uint32_t pf = A_PHI + ((lane >> 3) & 1) * kHalf + w * kPair + (lane >> 4) * 512 + (lane & 7) * 16;
#pragma unroll 1
  for (int tk = 0; tk < 2; tk++) {
    const int task = uniform(tk);
    if (task == 0) {
      mbar_wait(BAR_TOK + 8 * wg, 0);
    } else {
      uint32_t b[4][20];
#pragma unroll
      for (int i = 0; i < 5 * KV_PF; i++) ldsm4t(pf + (i % 5) * 1024 + (i / 5) * 128, b[i / 5] + 4 * (i % 5));
      mbar_wait(KPAUSE && wg ? BAR_PA : BAR_TOK + 8 * wg, KPAUSE ? wg ^ 1 : 1);
      TS(5 + 16 * wg);
      float acc[80];
#pragma unroll
      for (int i = 0; i < 80; i++) acc[i] = 0.f;
      constexpr int LA = KV_PF ? KV_PF : 1;
#pragma unroll
      for (int ks = KV_PF ? 0 : -1; ks < 4; ks++)
#pragma unroll
        for (int cp = 0; cp < 5; cp++) {
          if (ks + LA < 4) ldsm4t(pf + cp * 1024 + (ks + LA) * 128, b[ks + LA] + 4 * cp);
          if (ks + LA == 3 && cp == 4) mbar_arrive1(BAR_FREE + 8 * wg);
          if (ks >= 0) {
#pragma unroll
            for (int c = 2 * cp; c < 2 * cp + 2; c++) {
              const uint32_t* a = hold + (c < 5 ? 0 : 16) + 4 * ks;
              mma16(acc + 8 * c, a[0], a[1], a[2], a[3], b[ks][2 * c], b[ks][2 * c + 1]);
              mma16(acc + 8 * c + 4, hold[32 + 4 * ks], hold[33 + 4 * ks], hold[34 + 4 * ks], hold[35 + 4 * ks], b[ks][2 * c], b[ks][2 * c + 1]);
            }
          }
        }
      if (KPAUSE) {
        reg_fence<80>(acc);
        mbar_poll(BAR_V);
        mbar_arrive1(wg ? BAR_PA + 8 : BAR_DUMMY);
      }
      TS(46 + 2 * wg);
      uint32_t f[32];
#pragma unroll
      for (int c = 0; c < 10; c++) {
        const float* x = acc + 8 * c;
        const int h2 = c / 5, i = (c + 4 * h2) % 5, st = i < 4 ? 4 : 1, o = 16 * h2 + (i < 4 ? i : 12);
        const bool isv = (gi >> 2) == h2;
        f[o] = pack2(x[0], x[1]);
        f[o + st] = pack2(x[2], x[3]);
        f[o + 2 * st] = pack2(isv ? x[4] : x[6], isv ? x[5] : x[7]);
      }
      f[15] = f[31] = 0;
#pragma unroll
      for (int i = 0; i < 8; i++) sts128(A_PHI + kHalf + w * kPair + i * 512 + lane * 16, f[4 * i], f[4 * i + 1], f[4 * i + 2], f[4 * i + 3]);
      fence_async_smem();
      mbar_arrive1(BAR_RED + 8 * wg);
      if (KPAUSE) mbar_wait(BAR_TOK + 8 * wg, 1);
    }
    if (TA0 | TA1 | TA2) pace(c0, task ? (wg ? TA2 : TA1) : TA0);
    TS(3 + 3 * task + 16 * wg);
    float acc[76];
    a_mainloop152(acc, BAR_TOK + 8 * (wg ^ 1));
    wg_wait<0>();
    reg_fence<76>(acc);
    if (lane < 2) mbar_arrive(BAR_EMPTY + 32);
    if (task & wg) mbar_arrive1(BAR_QD);
    TS(4 + 3 * task + 16 * wg);

    uint32_t pa = A_PHI + q * kPair + (8 * w + gi) * 16;
    uint32_t gate = task ? (wg ? BAR_QF : BAR_FREE + 8) : (wg ? BAR_FREE : BAR_V);
    const uint32_t gate1 = task ? (wg ? BAR_QF1 : BAR_STG1) : (wg ? BAR_STG : BAR_V);
#pragma unroll
    for (int hh = 0; hh < 2; hh++) {
      float mx[2], mn[2];
      softmax_stats(acc + 2 * hh, mx[0], mn[0]);
      softmax_stats(acc + 2 * hh + 1, mx[1], mn[1]);
      mbar_wait(hh ? gate1 : gate, 0);
      softmax_group(acc + 2 * hh, mx[0], mn[0], pa + hh * kHalf);
      softmax_group(acc + 2 * hh + 1, mx[1], mn[1], pa + hh * kHalf + 2560);
      mbar_arrive1(task ? BAR_QS + 16 * wg + 8 * hh : BAR_DUMMY);
    }
    TS(56 + task + 2 * wg);
    if (task == 0) wg_bar(wg);
    TS(14 + task + 16 * wg);
  }
#pragma unroll 1
  for (int jb = J1 * wg; jb < J1 + (4 - J1) * wg; jb++) {
    const int job = uniform(jb), ty = job >> 1, hi = job & 1;
    mbar_wait(BAR_QS + 8 * job, 0);
    uint32_t aa[2][20];
    const uint32_t pn = A_PHI + hi * kHalf + w * kPair + (lane >> 4) * 512 + (lane & 15) * 16;
#pragma unroll
    for (int i = 0; i < 10; i++) ldsm4(pn + ((i + 2) % 5) * 1024 + (i / 5) * 256, aa[i / 5] + 4 * ((i + 2) % 5));
    mbar_arrive1(ty ? BAR_DUMMY : hi ? BAR_QF1 : BAR_QF);
    if (!hi || job == J1) {
      mbar_wait(BAR_KVR + 8 * ty, 0);
#pragma unroll
      for (int i = 0; i < 8; i++) {
        const uint32_t ka = (ty ? A_KV1 : A_KV0) + w * 4096 + i * 512 + lane * 16;
        lds128(ka, hold + 4 * i);
        if (KV_R == 2) {
          uint32_t x[4];
          lds128(ka + kKvBytes, x);
#pragma unroll
          for (int k = 0; k < 4; k++) asm("add.rn.bf16x2 %0, %0, %1;" : "+r"(hold[4 * i + k]) : "r"(x[k]));
        }
      }
      if (job == 0) {
        wg_bar(0);
        mbar_wait(BAR_TOK, 0);
      }
    }
    TS(8 + job - 3 * wg + 16 * wg);
    const uint32_t oa = A_X + ty * kBlob + (5 * w + (lane >> 4)) * 1024 + ((lane & 7) + 2 * (lane & 8) + 8 * hi) * 16;
#pragma unroll
    for (int u = 0; u < 2; u++) {
      const uint32_t* a = aa[u];
      float d[2][12];
#pragma unroll
      for (int h2 = 0; h2 < 2; h2++) {
        const uint32_t* b = hold + 16 * h2;
#pragma unroll
        for (int i = 0; i < 12; i++) d[h2][i] = 0.f;
        const uint32_t* a8 = a + 8 + 2 * h2;
        const uint32_t* a16 = a + 12 * h2;
#pragma unroll
        for (int j = 2; j >= 0; j--) {
          mma8(d[h2] + 4 * j, a8[0], a8[1], b[12 + j]);
          mma16(d[h2] + 4 * j, a16[0], a16[1], a16[2], a16[3], b[4 * j], b[4 * j + 1]);
          mma16(d[h2] + 4 * j, a16[4], a16[5], a16[6], a16[7], b[4 * j + 2], b[4 * j + 3]);
        }
      }
      uint32_t o[10];
#pragma unroll
      for (int hh = 0; hh < 2; hh++) {
        const bool up = q & 2;
        const float r0 = rcp((up ? d[0][8 + 2 * hh] : d[1][8 + 2 * hh]) + 1e-6f);
        const float r1 = __shfl_xor_sync(~0u, r0, 2);
        const float ra = up ? r0 : r1, rb2 = up ? r1 : r0;
        o[0 + hh] = pack2(d[0][2 * hh] * ra, d[0][2 * hh + 1] * ra);
        o[2 + hh] = pack2(d[0][4 + 2 * hh] * ra, d[0][5 + 2 * hh] * ra);
        o[4 + hh] = pack2((up ? d[1][8 + 2 * hh] : d[0][8 + 2 * hh]) * r1, (up ? d[1][9 + 2 * hh] : d[0][9 + 2 * hh]) * r1);
        o[6 + hh] = pack2(d[1][2 * hh] * rb2, d[1][2 * hh + 1] * rb2);
        o[8 + hh] = pack2(d[1][4 + 2 * hh] * rb2, d[1][5 + 2 * hh] * rb2);
      }
      stsm4(oa + u * 512, o[0], o[1], o[2], o[3]);
      stsm4(oa + u * 512 + 2048, o[4], o[5], o[6], o[7]);
      stsm2(oa + u * 512 + 4096, o[8], o[9]);
    }
    fence_async_smem();
    mbar_arrive1(BAR_O + 8 * ty);
  }
  float acc[80];
#pragma unroll
  for (int i = 0; i < 80; i++) acc[i] = 0.f;
  reg_fence<80>(acc);
#pragma unroll 1
  for (int rr = wg ^ 1; rr <= P.one; rr++) {
    const int r = uniform(rr);
    mbar_wait(r ? BAR_TOK + 8 * wg : BAR_O + 8, r & ~wg);
    TS(9 + 3 * r + 16 * wg);
    a_mainloop160(acc, desc_lo(A_X, 1024) + (r & wg) * 2560, r, 2 - wg, (r & wg) ? BAR_P1 : BAR_O + 8, BAR_TOK + 8 * (wg ^ 1));
    wg_wait<0>();
    reg_fence<80>(acc);
    if (lane < 2) mbar_arrive(BAR_EMPTY + 32);
    TS(10 + 3 * r + 16 * wg);
  }
  float* o = P.out + (size_t)(rb * 64 + 16 * w + gi) * 1280 + 160 * hg + 4 * q;
#pragma unroll
  for (int jp = 0; jp < 10; jp++) {
#pragma unroll
    for (int hh = 0; hh < 2; hh++)
      *reinterpret_cast<float4*>(o + hh * 8 * 1280 + 16 * jp) =
          make_float4(acc[8 * jp + 2 * hh], acc[8 * jp + 2 * hh + 1], acc[8 * jp + 4 + 2 * hh], acc[8 * jp + 5 + 2 * hh]);
    if (A_SLEEP && jp < 9) __nanosleep(wg ? 0 : A_SLEEP);
  }
  TS(32 + wg);
}

__device__ __forceinline__ void fold_load(const Params& P, int job, uint32_t buf, uint32_t bar, uint32_t bar_phi) {
  const int grp = job / 10, kb = job - 10 * grp;
  const int col = (grp & 3) * 160 + (grp < 4 ? 640 : 0);
  mbar_expect(bar_phi, kPrepPhi);
  bulk_load(buf + kPrepW, P.wphi + (grp & 3) * 3200, kPrepPhi, bar_phi);
  mbar_expect(bar, kPrepW);
#pragma unroll
  for (int i = 0; i < 3; i++) tma5d(buf + i * 8192, &P.wp, col + i * 64, 0, 0, 0, 2 * kb, bar);
}
__device__ __forceinline__ void wo_load(const Params& P, int job, uint32_t buf, uint32_t bar) {
  const int ns = job / 10, kb = job - 10 * ns;
  mbar_expect(bar, kPrepW);
#pragma unroll 1
  for (int i = 0; i < 6; i++) {
    const int u = 2 * kb + (i & 1), pos = u / 5;
    tma5d(buf + i * 4096, &P.wop, ns * 160 + (i >> 1) * 64, 0, 0, 0, 5 * (2 * (((ns ^ pos) >> 1) & 1) + 1 - (pos & 1) - pos) + u, bar);
  }
}

__device__ __forceinline__ void prep_fold(uint32_t buf, uint32_t bar, uint32_t bar_phi, long long t_start) {
  const int tid = threadIdx.x, hl = tid >> 5, lane = tid & 31, gi = lane >> 2, q = lane & 3;
  const int dq = 2 * q - 4 * (hl & 1);
  const uint32_t wq = buf + kPrepW + hl * 800 + dq * 40, wp = wq + gi * 2 + 2;
  uint32_t fa[12];
  mbar_wait(bar_phi, 0);
#pragma unroll
  for (int dg = 0; dg < 3; dg++)
#pragma unroll
    for (int fg = 0; fg < 4; fg++) {
      uint32_t lo, hi;
      asm volatile("ld.shared.u16 %0, [%2];\nld.shared.u16 %1, [%2+40];" : "=r"(lo), "=r"(hi) : "r"(fg < 3 ? wp + dg * 320 + fg * 16 : wq + dg * 320) : "memory");
      const uint32_t x = __byte_perm(lo, hi, 0x5410);
      fa[4 * dg + fg] = (dg == 1 || (unsigned)(dq + 8 * dg) < 20u) ? x : 0u;
    }
  mbar_wait(bar, 0);
  TS(7 + 16 * (hl >> 2));
  uint32_t b[2][3][4];
#pragma unroll
  for (int dg = 2; dg >= 0; dg--) {
    const int c = ((5 * hl) >> 1) + dg;
    const uint32_t a = buf + (c >> 3) * 8192 + lane * 128 + (((c ^ lane) & 7) << 4);
    ldsm4(a, b[0][dg]);
    ldsm4(a + 4096, b[1][dg]);
  }
  asm volatile("bar.sync 3, 256;" ::: "memory");
#pragma unroll
  for (int th = 0; th < 2; th++) {
    uint32_t r[3][4];
#pragma unroll
    for (int tt = 0; tt < 4; tt++) {
      float d0[4] = {0.f, 0.f, 0.f, 0.f}, d1[4] = {0.f, 0.f, 0.f, 0.f};
      mma8(d0, fa[8], fa[9], b[th][2][tt]);
      mma16(d0, fa[0], fa[1], fa[4], fa[5], b[th][0][tt], b[th][1][tt]);
      mma8(d1, fa[10], fa[11], b[th][2][tt]);
      mma16(d1, fa[2], fa[3], fa[6], fa[7], b[th][0][tt], b[th][1][tt]);
      r[0][tt] = pack2(d0[0] - d1[2], d0[1] - d1[3]);
      r[1][tt] = pack2(d0[2] - d1[2], d0[3] - d1[3]);
      r[2][tt] = pack2(d1[0] - d1[2], d1[1] - d1[3]);
    }
    const uint32_t dst = buf + (8 * gi + hl) * 128 + (((4 * th + q) ^ hl) << 4);
#pragma unroll
    for (int fg = 0; fg < 3; fg++) sts128(dst + fg * 8192, r[fg][0], r[fg][1], r[fg][2], r[fg][3]);
  }
  fence_async_smem();
}

__device__ __forceinline__ void prep_wo(uint32_t buf) {
  const int tid = threadIdx.x & 127, w = tid >> 5, lane = tid & 31, gi = lane >> 2, q = lane & 3;
  const int th = w & 1, c0 = w >> 1;
  uint32_t v[10][4];
#pragma unroll
  for (int i = 0; i < 10; i++)
    ldsm4t(buf + (i >> 2) * 8192 + th * 4096 + lane * 128 + ((((2 * i + c0) ^ lane) & 7) << 4), v[i]);
  wg_bar(1);
  const int row = 4 * (gi & 2) + 4 * c0 + 2 * (gi >> 2) + (gi & 1);
  const uint32_t dst = buf + row * 128 + ((((4 * th + q) ^ row) & 7) << 4);
#pragma unroll
  for (int i = 0; i < 10; i++) sts128(dst + i * 2048, v[i][0], v[i][1], v[i][2], v[i][3]);
  fence_async_smem();
}

__device__ __forceinline__ void b_producer_w(const Params& P, int g, long long t_start) {
  const uint32_t c0 = clock();
#pragma unroll 1
  for (int r = 0; r < 4; r++) {
    const int row = g * 128 + (r >> 1) * 64, k0 = (r & 1) * 320;
#pragma unroll
    for (int s = 0; s < 5; s++) {
      if (r == 0) pace(c0, B_PACE0 + s * B_PACE);
      mbar_wait(BAR_EMPTY + 8 * s, (r & 1) ^ 1);
      ST(64 + 5 * r + s);
      mbar_expect(BAR_FULL + 8 * s, 16384);
      tma2d(B_RING + s * B_SLOT, &P.bre, k0 + s * 64, row, BAR_FULL + 8 * s);
      tma2d(B_RING + s * B_SLOT + 8192, &P.bim, k0 + s * 64, row, BAR_FULL + 8 * s);
    }
  }
#pragma unroll 1
  for (int ty = 0; ty < 2; ty++) {
#pragma unroll
    for (int st = 0; st < 10; st++) {
      const int s = st % 5, i = (st >> 1) - 1;
      mbar_wait(BAR_EMPTY + 8 * s, st < 5);
      ST(84 + 10 * ty + st);
      if (st == 6) mbar_arrive1(BAR_W + 8 + 8 * ty);
      mbar_expect(BAR_FULL + 8 * s, 16384);
      tma5d(B_RING + s * B_SLOT, (st & 1) ? &P.cim : &P.cre, (i < 0 ? g : i < g ? i : i + 1) * 128 + ty * 64, 0, 0, 4 * g, 0, BAR_FULL + 8 * s);
    }
  }
}

__device__ __forceinline__ void b_producer_x(const Params& P, int tb, int g, long long t_start) {
  const uint32_t c0 = clock();
  const unsigned ep_raw = load_epoch_raw(P);
  const CUtensorMap* xm = tb < 12 ? &P.xb : &P.xbl;
  const int xj = tb < 12 ? 0 : -4, xb = tb < 12 ? tb : 0;
#pragma unroll 1
  for (int r = 0; r < 4; r++) {
#pragma unroll
    for (int s = 0; s < 5; s++) {
      if (r == 0) pace(c0, B_PACE0 + s * B_PACE);
      mbar_wait(BAR_EMPTY + 8 * s, (r & 1) ^ 1);
      ST(5 * r + s);
      mbar_expect(BAR_FULL + 8 * s, kBlob);
      tma5d(B_RING + s * B_SLOT + 16384, xm, (r & 1) * 320 + s * 64, 0, 0, xj, xb, BAR_FULL + 8 * s);
    }
  }
#pragma unroll 1
  for (int ty = 0; ty < 2; ty++) {
    const unsigned char* src = P.s->h + (size_t)(tb * 20 + ty * 10) * kBlob;
    uint32_t have = 0;
    mbar_wait(BAR_O + 8 * ty, 0);
#pragma unroll
    for (int st = 0; st < 10; st++) {
      const int s = st % 5, i = (st >> 1) - 1;
      if (st >= 2 && !(st & 1)) {
        if (st == 2 && H_GATE) mbar_wait(BAR_STG, ty);
        if (st == 2) TS1(40 + 2 * ty);
        const uint32_t need = H_ALL ? 31 : i < g ? 1 << i : 2 << i;
        if ((have & need) != need) have = uniform(line_wait(P, C_H + (2 * tb + ty) * 32, ep_raw + 1, need, 0));
        if (st == 2) TS1(41 + 2 * ty);
      }
      mbar_wait(BAR_EMPTY + 8 * s, st < 5);
      ST(20 + 10 * ty + st);
      if (st < 2) {
        mbar_arrive1(BAR_FULL + 8 * s);
      } else {
        mbar_expect(BAR_FULL + 8 * s, kBlob);
        bulk_load(B_RING + s * B_SLOT + 16384, src + (st - (i < g ? 2 : 0)) * kBlob, kBlob, BAR_FULL + 8 * s);
      }
    }
  }
}

__device__ __forceinline__ void b_helper(const Params& P, int bi, int tb, int g, long long t_start) {
  const uint32_t c0 = clock();
#pragma unroll 1
  for (int job = bi; job < 120; job += 80) {
    if (job >= 80) {
      while ((uint32_t)clock() - c0 < WO_T) __nanosleep(100);
      wo_load(P, bi, B_STG, BAR_P1);
    }
    mbar_wait(job < 80 ? BAR_PREP : BAR_FREE, 0);
    bulk_store(P.s->w + (size_t)tile_pos(job) * kBlob, B_STG, kBlob);
    if (job < 40 && job % 10 < 8) {
#pragma unroll
      for (int i = 0; i < KV_R; i++) bulk_store(P.s->kv + ((job - job / 10 * 2) * KV_R + i) * 2048, B_ZERO, 2048);
    }
    bulk_wait();
    cnt_add(P, tile_counter(job));
    TS1(job < 80 ? 34 : 35);
  }
  mbar_arrive1(BAR_KVR);
  mbar_wait(BAR_TOK + 8, 0);
  if (bi < 64) {
    prefetch_l2(P.cre_p + bi * 6400, 12800);
    prefetch_l2(P.cim_p + bi * 6400, 12800);
  }
#pragma unroll 1
  for (int ty = 0; ty < 2; ty++) {
    unsigned char* dst = P.s->h + (size_t)(tb * 20 + ty * 10 + 2 * g) * kBlob;
#pragma unroll
    for (int c = 0; c < 5; c++) {
      const uint32_t lo = c ? h_end(c - 1) * 1024 : 0, n = h_end(c) * 1024 - lo;
      mbar_wait(c == 4 ? BAR_O + 8 * ty : BAR_X + 8 * (5 * ty + c), 0);
      bulk_store(dst + lo, B_STG + lo, n);
      bulk_store(dst + kBlob + lo, B_STG + kBlob + lo, n);
    }
    bulk_wait();
    mbar_arrive1(BAR_STG);
    TS1(46 + ty);
    cnt_add(P, C_H + (2 * tb + ty) * 32 + g);
    TS1(44 + ty);
  }
  mbar_expect(BAR_W, 2 * kBlob);
  mbar_wait(BAR_W + 16, 0);
#pragma unroll
  for (int i = 0; i < 2; i++) tma5d(B_STG + i * kBlob, tb < 12 ? &P.xb : &P.xbl, g * 128 + 64 * i, 0, 0, tb < 12 ? 0 : -4, tb < 12 ? tb : 0, BAR_W);
}

__device__ __forceinline__ void cmul(float ar, float ai, float br, float bi, float& cr, float& ci) {
  const float r = fmaf(ar, br, -ai * bi), i = fmaf(ar, bi, ai * br);
  cr = r; ci = i;
}
__device__ __forceinline__ void cstep(float mr, float mi, float& hr, float& hi, float er, float ei) {
  const float r = fmaf(mr, hr, fmaf(-mi, hi, er)), i = fmaf(mr, hi, fmaf(mi, hr, ei));
  hr = r; hi = i;
}
__device__ __forceinline__ void quad_gather(const float* f, int q, float* o) {
  const bool b0 = q & 1, b1 = q & 2;
  const float mine = b0 ? f[1] : f[0];
  const float r = __shfl_xor_sync(~0u, b0 ? f[0] : f[1], 1);
  const float lo = b0 ? r : mine, hi = b0 ? mine : r;
  const float lo2 = __shfl_xor_sync(~0u, lo, 2), hi2 = __shfl_xor_sync(~0u, hi, 2);
  o[0] = b1 ? lo2 : lo; o[1] = b1 ? hi2 : hi; o[2] = b1 ? lo : lo2; o[3] = b1 ? hi : hi2;
}
__device__ __forceinline__ void quad_scatter(const float* s, int q, float* f) {
  const bool b0 = q & 1, b1 = q & 2;
  const float lo = b1 ? s[2] : s[0], hi = b1 ? s[3] : s[1];
  const float mine = b0 ? hi : lo;
  const float r = __shfl_xor_sync(~0u, b0 ? lo : hi, 1);
  f[0] = b0 ? r : mine; f[1] = b0 ? mine : r;
}

__device__ __forceinline__ void b_consumer(const Params& P, int bi, int tb, int g, int wg, uint32_t c0, long long t_start) {
  const int tid = threadIdx.x & 127, w = tid >> 5, lane = tid & 31, gi = lane >> 2, q = lane & 3;
  const bool last = tb == 12;

  if (wg) {
    mbar_arrive1(BAR_TOK);
    const int p = 128 * g + tid;
    const float are = ldbf(P.lre + p), aim = ldbf(P.lim + p), ldt = ldbf(P.logdt + p);
    const float dt = __bfloat162float(__float2bfloat16_rn(expf(ldt)));
    const float mag = expf(dt * are);
    float sn, cs;
    sincospif(dt * aim * 0.3183098861837907f, &sn, &cs);
    const float lr = mag * cs, li = mag * sn;
    const float inv = 2.0f * rcp(fmaf(are, are, aim * aim));
    float mr, mi, nr, ni;
    cmul(lr, li, lr, li, nr, ni);
    cmul(nr, ni, nr, ni, nr, ni);
    cmul(nr, ni, nr, ni, nr, ni);
    cmul(nr, ni, nr, ni, mr, mi);
    cmul(mr, mi, mr, mi, mr, mi);
    if (!last) cmul(mr, mi, nr, ni, mr, mi);
    sts128(B_CONST + tid * 16, __float_as_uint(lr), __float_as_uint(li), __float_as_uint(fmaf(lr - 1.0f, are, li * aim) * inv),
           __float_as_uint(fmaf(li, are, (1.0f - lr) * aim) * inv));
    asm volatile("st.shared.v2.f32 [%0], {%1,%2};" ::"r"(B_CONST + 2048 + tid * 8), "f"(mr), "f"(mi) : "memory");
    asm volatile("st.shared.u32 [%0], %1;" ::"r"(B_CONST + 3072), "r"((load_epoch_raw(P) + 1) & 3) : "memory");
    mbar_arrive1(BAR_V);
    if (bi < 40) {
      mbar_wait(BAR_P1, 0);
      prep_wo(B_STG);
      mbar_arrive1(BAR_FREE);
    }
  }

  float u[80], v[80];
  reg_kill<80>(u);
  reg_kill<80>(v);
#pragma unroll 1
  for (int it = 0;; it++) {
    const int task = uniform(it);
    mbar_wait(BAR_TOK + 8 * wg, task);
    TS((task ? 9 : 1) + 16 * wg);
    b_mainloop(u, v, 10 + 10 * task, task ? 0xc03 : 0, BAR_TOK + 8 * (wg ^ 1));
    wg_wait<0>();
    reg_fence<80>(u);
    reg_fence<80>(v);
    TS((task ? 12 : 2) + 16 * wg);
    if (task) break;
    mbar_arrive1(BAR_EMPTY + 32);

    const int pl = 64 * wg + 16 * w + gi, p = 128 * g + pl + 8 * (q & 1);
    uint32_t tag, k0[4], k1[4];
    float mr, mi;
    mbar_wait(BAR_V, 0);
    asm volatile("ld.shared.u32 %0, [%1];" : "=r"(tag) : "r"(B_CONST + 3072) : "memory");
    lds128(B_CONST + pl * 16, k0);
    lds128(B_CONST + pl * 16 + 128, k1);
    asm volatile("ld.shared.v2.f32 {%0,%1}, [%2];" : "=f"(mr), "=f"(mi) : "r"(B_CONST + 2048 + (pl + 8 * (q & 1)) * 8) : "memory");
    const float Lr[2] = {__uint_as_float(k0[0]), __uint_as_float(k1[0])}, Li[2] = {__uint_as_float(k0[1]), __uint_as_float(k1[1])};
    const float Cr[2] = {__uint_as_float(k0[2]), __uint_as_float(k1[2])}, Ci[2] = {__uint_as_float(k0[3]), __uint_as_float(k1[3])};
    float hr[2] = {0.f, 0.f}, hi[2] = {0.f, 0.f};
#pragma unroll
    for (int t = 0; t < 40; t++)
#pragma unroll
      for (int a = 0; a < 2; a++) {
        const int r = 4 * (t >> 1) + 2 * a + (t & 1);
        cstep(Lr[a], Li[a], hr[a], hi[a], u[r], v[r]);
      }
    float fr[4], fi[4];
    quad_gather(hr, q, fr);
    quad_gather(hi, q, fi);
    float sr = fr[0], si = fi[0];
#pragma unroll
    for (int a = 1; a < 4; a++) cstep(mr, mi, sr, si, fr[a], fi[a]);
    unsigned long long* fin = P.s->fin + tb * 640 + p;
    if (q < 2)
      asm volatile("st.relaxed.gpu.global.v2.b32 [%0], {%1, %2};" ::"l"(fin), "r"((__float_as_uint(sr) & ~3u) | tag), "r"((__float_as_uint(si) & ~3u) | tag) : "memory");
    TS(3 + 16 * wg);
    reg_fence<80>(u);
    reg_fence<80>(v);
#pragma unroll
    for (int a = 0; a < 2; a++) {
      const float kr = Cr[a], ki = Ci[a];
#pragma unroll
      for (int t = 0; t < 40; t++) {
        const int r = 4 * (t >> 1) + 2 * a + (t & 1);
        const float xr = u[r], xi = v[r];
        u[r] = fmaf(kr, xr, -ki * xi);
        v[r] = fmaf(-kr, xi, -ki * xr);
      }
    }
    reg_fence<80>(u);
    reg_fence<80>(v);
    float nr, ni, fr6, fi6;
    cmul(mr, mi, mr, mi, nr, ni);
    cmul(nr, ni, nr, ni, nr, ni);
    if (last) cmul(nr, ni, mr, mi, nr, ni);
    cmul(nr, ni, nr, ni, fr6, fi6);
    cmul(fr6, fi6, nr, ni, fr6, fi6);
    cmul(fr6, fi6, fr6, fi6, fr6, fi6);
    if (q & 2) { fr6 = 1.f; fi6 = 0.f; }
    uint32_t er[6], ei[6];
#pragma unroll
    for (int k = 0; k < 6; k++) er[k] = ei[k] = tag;
    const int back = (q & 2) ? 6 : 12;
    fin -= back * 640;
    uint32_t bad;
    do {
      bad = 0;
#pragma unroll
      for (int k = 0; k < 6; k++)
        asm volatile("{ .reg .pred p; setp.le.s32 p, %3, %4;\n@p ld.relaxed.gpu.global.v2.b32 {%0, %1}, [%2]; }"
                     : "+r"(er[k]), "+r"(ei[k]) : "l"(fin + k * 640), "r"(back - tb), "r"(k) : "memory");
#pragma unroll
      for (int k = 0; k < 6; k++) bad |= (er[k] ^ tag) | (ei[k] ^ tag);
    } while (__any_sync(~0u, bad & 3));
    sr = 0.f; si = 0.f;
#pragma unroll
    for (int k = 0; k < 6; k++) cstep(nr, ni, sr, si, __uint_as_float(er[k] ^ tag), __uint_as_float(ei[k] ^ tag));
    cmul(fr6, fi6, sr, si, sr, si);
    sr += __shfl_xor_sync(~0u, sr, 2);
    si += __shfl_xor_sync(~0u, si, 2);
    TS(4 + 16 * wg);
#pragma unroll
    for (int a = 0; a < 4; a++) {
      const float xr = sr, xi = si;
      cstep(mr, mi, sr, si, fr[a], fi[a]);
      fr[a] = xr; fi[a] = xi;
    }
    quad_scatter(fr, q, hr);
    quad_scatter(fi, q, hi);
#pragma unroll
    for (int a = 0; a < 2; a++) {
      const float xr = hr[a], xi = hi[a];
      hr[a] = fmaf(Cr[a], xr, -Ci[a] * xi);
      hi[a] = fmaf(-Cr[a], xi, -Ci[a] * xr);
    }
    if (last) {
#pragma unroll
      for (int a = 0; a < 2; a++) {
        u[13 + 2 * a] = hr[a]; v[13 + 2 * a] = hi[a];
        hr[a] = 0.f; hi[a] = 0.f;
      }
    }
    const uint32_t ha = B_STG + (lane >> 4) * kBlob + (lane & 7) * 128 + (((2 * w + ((lane >> 3) & 1)) ^ (lane & 7)) << 4);
    if (B_SPLIT) {
#pragma unroll
      for (int t = 0; t < 40; t++)
#pragma unroll
        for (int a = 0; a < 2; a++) {
          const int r = 4 * (t >> 1) + 2 * a + (t & 1);
          cstep(Lr[a], -Li[a], hr[a], hi[a], u[r], v[r]);
          u[r] = hr[a]; v[r] = hi[a];
        }
      reg_fence<80>(u);
      reg_fence<80>(v);
    }
    mbar_wait(wg ? BAR_STG : BAR_KVR, 0);
    TS(5 + 16 * wg);
    if (wg) mbar_wait(BAR_W + 8, 0);
    TS(6 + 16 * wg);
#pragma unroll
    for (int j = 0; j < 20; j++) {
      uint32_t kr[2], ki[2];
#pragma unroll
      for (int a = 0; a < 2; a++) {
        const int r = 4 * j + 2 * a;
        if (B_SPLIT) {
          kr[a] = pack2(u[r], u[r + 1]);
          ki[a] = pack2(v[r], v[r + 1]);
        } else {
          cstep(Lr[a], -Li[a], hr[a], hi[a], u[r], v[r]);
          const float xr = hr[a], xi = hi[a];
          cstep(Lr[a], -Li[a], hr[a], hi[a], u[r + 1], v[r + 1]);
          kr[a] = pack2(xr, hr[a]);
          ki[a] = pack2(xi, hi[a]);
        }
      }
      stsm4t(ha + j * 1024, kr[0], kr[1], ki[0], ki[1]);
#pragma unroll
      for (int c = 0; c < 4; c++)
        if (j + 1 == h_end(c)) {
          fence_async_smem();
          mbar_arrive1(BAR_X + 8 * (5 * wg + c));
        }
    }
    fence_async_smem();
    mbar_arrive1(BAR_O + 8 * wg);
    TS(8 + 16 * wg);
    if (wg) return;
  }

  const int dl = 32 * w + 4 * gi;
  const uint2 dk = __ldg(reinterpret_cast<const uint2*>(P.dskip + 128 * g + dl));
  const float k0 = bf_lo(dk.x), k1 = bf_hi(dk.x), k2 = bf_lo(dk.y), k3 = bf_hi(dk.y);
  float* o = P.out + (size_t)(last ? 1920 + 32 * q - 8 : 160 * tb + 40 * q) * 1280 + 640 + 128 * g + dl;
  const uint32_t xa = B_STG + (w >> 1) * kBlob + q * 256 + (gi & 1) * 8;
  const uint32_t xc = (4 * (w & 1) + (gi >> 1)) ^ (2 * q);
  mbar_wait(BAR_W, 0);
#pragma unroll
  for (int t = 0; t < 40; t++) {
    const int r = 4 * (t >> 1) + (t & 1);
    uint32_t x0, x1;
    asm volatile("ld.shared.v2.b32 {%0,%1}, [%2];" : "=r"(x0), "=r"(x1) : "r"(xa + (t >> 1) * 1024 + (t & 1) * 128 + ((xc ^ (t & 1)) << 4)));
    asm volatile("{ .reg .pred p; setp.ne.s32 p, %5, 0;\n@p st.global.v4.f32 [%0], {%1, %2, %3, %4}; }" ::"l"(o + t * 1280),
                 "f"(fmaf(bf_lo(x0), k0, u[r])), "f"(fmaf(bf_hi(x0), k1, u[r + 2])), "f"(fmaf(bf_lo(x1), k2, v[r])), "f"(fmaf(bf_hi(x1), k3, v[r + 2])),
                 "r"((int)(t >= 8 || !last)));
  }
  TS(15);
}

__global__ void __launch_bounds__(kThreads, 1) fused_kernel(const __grid_constant__ Params P) {
  extern __shared__ __align__(1024) unsigned char smem[];
  const long long t_start = 0;
  const int b = blockIdx.x;
  const uint32_t c0 = clock();
  const bool isA = b < 128 && (b & 2), isB = !isA && b <= 128;
  const int idx = b < 128 ? (b >> 2) * 2 + (b & 1) : b - 64;
  const int warp = uniform(threadIdx.x >> 5), wg = warp >> 2;
  if (warp == 8) {
    if (threadIdx.x == 256) {
#pragma unroll
      for (int i = 0; i < A_PRE; i++) mbar_init(BAR_FULL + 8 * i, isB ? 2 : 1);
      if (isA) {
#pragma unroll
        for (int i = 0; i < A_PRE - 1; i++) mbar_init(BAR_X + 8 * i, 1);
      } else {
        mbar_init(BAR_P, 1);
        mbar_init(BAR_KV0, 1);
      }
      asm volatile("fence.mbarrier_init.release.cluster;" ::: "memory");
    }
    __syncwarp();
    if (isB) fold_load(P, idx, B_STG, BAR_P, BAR_KV0);
    if (isA) {
#pragma unroll
      for (int n = 0; n < A_PRE; n++) {
        if (n != 1) {
          const int kb = n ? n - 1 : 0;
          mbar_expect(BAR_X + 8 * kb, 8192);
          tma2d(A_X + kb * 8192, &P.xa, kb * 64, (idx & 31) * 64, BAR_X + 8 * kb);
        }
        mbar_expect(BAR_FULL + 8 * n, kBlob);
        tma3d(A_RING + n * kBlob, &P.wv, 0, n * 32, 20 + 5 * (idx >> 5), BAR_FULL + 8 * n);
        if (n == A_PF && (unsigned)((idx & 31) - A_PRE) < 20 - A_PRE) prefetch3d(&P.wv, 0, (idx & 31) * 32, 20 + 5 * (idx >> 5));
      }
    }
    TS1(38);
  } else if (threadIdx.x == 288) {
#pragma unroll
    for (uint32_t a = BAR_FULL + 8 * A_PRE; a < BAR_FREE; a += 8) {
      const uint32_t c = a < BAR_EMPTY ? (isB ? 2 : 1) : a < BAR_TOK ? (isB ? 4 : 8) : a >= BAR_X ? (isB ? 4 : 1)
                       : (a <= BAR_O + 8 && a != BAR_STG) ? (isA ? 8 : 4) : 1;
      const bool early_a = a >= BAR_X && a < BAR_X + 8 * (A_PRE - 1), early_b = a == BAR_P || a == BAR_KV0;
      if (early_a ? !isA : early_b ? isA : true) mbar_init(a, c);
    }
    asm volatile("fence.mbarrier_init.release.cluster;" ::: "memory");
  } else if (threadIdx.x == 320) {
#pragma unroll
    for (uint32_t a = BAR_FREE; a <= BAR_WA + 32; a += 8) mbar_init(a, bar_count(a));
    asm volatile("fence.mbarrier_init.release.cluster;" ::: "memory");
  }
  __syncthreads();
  const int rb = idx & 31, half = idx >> 5;
  const int tb = idx / 5, g = idx % 5;
  if (wg == 2) {
    asm volatile("setmaxnreg.dec.sync.aligned.u32 40;");
    if (warp == 8) {
      TS1(37);
      if (isA) a_producer(P, rb, half, t_start);
      else if (isB) b_producer_w(P, g, t_start);
      else {
#pragma unroll 1
        for (int n = 0; n < 5; n++) {
          pace(c0, P_PACE0 + n * P_PACE);
          fold_load(P, idx + 3 * n, B_RING + n * 32768, BAR_FULL + 8 * n, BAR_X + 8 * n);
        }
#pragma unroll 1
        for (int n = 0; n < 5; n++) {
          mbar_wait(BAR_EMPTY + 8 * n, 0);
          bulk_store(P.s->w + (size_t)tile_pos(idx + 3 * n) * kBlob, B_RING + n * 32768, kBlob);
        }
        bulk_wait();
        if (threadIdx.x < 261) asm volatile("red.release.gpu.global.add.u32 [%0], 1;" ::"l"(P.s->cnt + tile_counter(idx + 3 * (threadIdx.x - 256))) : "memory");
        __syncwarp();
        TS1(34);
      }
    } else if (warp < 11) {
      if (isA) {
        const unsigned ep = load_epoch(P);
        if (warp == 9) {
          a_helper(P, rb, half, ep, t_start);
        } else {
          a_poller(P, half, ep);
          a_exchange(P, rb, half, ep, t_start);
        }
        a_swap(P, rb, half, O_SWAP ? 10 - warp : warp - 9, ep, t_start);
      } else if (isB) {
        if (warp == 9) b_helper(P, idx, tb, g, t_start);
        else b_producer_x(P, tb, g, t_start);
      }
    } else {
      if ((uint32_t)__cvta_generic_to_shared(smem) != SB) __trap();
      const unsigned ep = load_epoch(P);
      const long long t0 = clock64();
      uint32_t ok;
      do {
        asm volatile("{ .reg .pred p; mbarrier.try_wait.parity.shared::cta.b64 p, [%1], 0, 100000; selp.u32 %0, 1, 0, p; }" : "=r"(ok) : "r"(BAR_DONE) : "memory");
        if (clock64() - t0 > 4000000000ll) __trap();
      } while (!ok);
      P.s->ep[b * 32] = ep;
    }
    if (warp < 11) mbar_arrive1(BAR_DONE);
  } else {
    asm volatile("setmaxnreg.inc.sync.aligned.u32 232;");
    if (isA) mbar_arrive1(BAR_TOK);
    if (isA) {
      a_consumer(P, rb, half, wg, c0, t_start);
    } else {
      if (threadIdx.x < 128) sts128(B_ZERO + threadIdx.x * 16, 0u, 0u, 0u, 0u);
#pragma unroll 1
      for (int n = 0; n < (isB ? 1 : 5); n++) {
        prep_fold(isB ? B_STG : B_RING + n * 32768, isB ? BAR_P : BAR_FULL + 8 * n, isB ? BAR_KV0 : BAR_X + 8 * n, t_start);
        mbar_arrive1(isB ? BAR_PREP : BAR_EMPTY + 8 * n);
      }
      if (isB) b_consumer(P, idx, tb, g, wg, c0, t_start);
    }
    mbar_arrive1(BAR_DONE);
  }
}

typedef CUresult (*EncodeFn)(CUtensorMap*, CUtensorMapDataType, cuuint32_t, void*, const cuuint64_t*, const cuuint64_t*,
                             const cuuint32_t*, const cuuint32_t*, CUtensorMapInterleave, CUtensorMapSwizzle,
                             CUtensorMapL2promotion, CUtensorMapFloatOOBfill);

void encode(EncodeFn fn, CUtensorMap* m, const void* ptr, int rank, const cuuint64_t* dims, const cuuint64_t* strides, const cuuint32_t* box, int promo = 2) {
  const cuuint32_t es[5] = {1, 1, 1, 1, 1};
  fn(m, CU_TENSOR_MAP_DATA_TYPE_BFLOAT16, rank, const_cast<void*>(ptr), dims, strides, box, es, CU_TENSOR_MAP_INTERLEAVE_NONE,
     CU_TENSOR_MAP_SWIZZLE_128B, (CUtensorMapL2promotion)promo, CU_TENSOR_MAP_FLOAT_OOB_FILL_NONE);
}

}

extern "C" void kernel_launch(void* const* d_in, const int* in_sizes, int n_in, void* d_out, int out_size) {
  (void)in_sizes; (void)n_in; (void)out_size;
  void* fp = nullptr;
  cudaDriverEntryPointQueryResult qr;
  cudaGetDriverEntryPoint("cuTensorMapEncodeTiled", &fp, cudaEnableDefault, &qr);
  EncodeFn fn = (EncodeFn)fp;
  const __nv_bfloat16* const* in = (const __nv_bfloat16* const*)d_in;
  Params P;
  constexpr cuuint64_t R = kD * 2;
  {
    const cuuint64_t d[2] = {kD, kSeq}, s[1] = {R};
    const cuuint32_t b[2] = {64, 64};
    encode(fn, &P.xa, in[0], 2, d, s, b, PR_XA);
  }
  {
    const cuuint64_t d[3] = {64, kD, 30}, s[2] = {3 * R, 128};
    const cuuint32_t b[3] = {64, 32, 5};
    encode(fn, &P.wv, in[1], 3, d, s, b);
  }
  {
    const cuuint64_t d[5] = {kD, 2, 4, 20, 12}, s[4] = {R, 40 * R, 2 * R, 160 * R};
    const cuuint32_t b[5] = {64, 2, 4, 20, 1};
    encode(fn, &P.xb, in[4], 5, d, s, b, PR_XB);
    const cuuint64_t dl[5] = {kD, 2, 4, 16, 1}, sl[4] = {R, 32 * R, 2 * R, 160 * R};
    encode(fn, &P.xbl, in[4] + 1920 * kD, 5, dl, sl, b, PR_XB);
  }
  {
    const cuuint64_t d[2] = {kD, kD}, s[1] = {R};
    const cuuint32_t b[2] = {64, 64};
    encode(fn, &P.bre, in[7], 2, d, s, b, PR_B);
    encode(fn, &P.bim, in[8], 2, d, s, b, PR_B);
  }
  {
    const cuuint64_t d[5] = {kD, 8, 2, 20, 2}, s[4] = {4 * R, R, 32 * R, 2 * R};
    const cuuint32_t b[5] = {64, 8, 2, 4, 2};
    encode(fn, &P.cre, in[9], 5, d, s, b);
    encode(fn, &P.cim, in[10], 5, d, s, b);
  }
  {
    const cuuint64_t d[5] = {3 * kD, 2, 4, 4, 20}, s[4] = {3 * R, 24 * R, 6 * R, 96 * R};
    const cuuint32_t b[5] = {64, 2, 4, 4, 1}, b2[5] = {64, 2, 4, 4, 2};
    encode(fn, &P.wp, in[1], 5, d, s, b2);
    const cuuint64_t d2[5] = {kD, 2, 4, 4, 20}, s2[4] = {R, 8 * R, 2 * R, 32 * R};
    encode(fn, &P.wop, in[3], 5, d2, s2, b);
  }
  P.wphi = in[2]; P.cre_p = in[9]; P.cim_p = in[10];
  P.lre = in[5]; P.lim = in[6]; P.logdt = in[11]; P.dskip = in[12];
  P.out = (float*)d_out;
  P.one = 1;
  cudaGetSymbolAddress((void**)&P.s, g_scratch);
  cudaFuncSetAttribute(fused_kernel, cudaFuncAttributeMaxDynamicSharedMemorySize, kSmem);
  fused_kernel<<<kGrid, kThreads, kSmem>>>(P);
}
```

```cpp
#include <cuda_runtime.h>
#include <cuda_bf16.h>
#include <cuda.h>
#include <stdint.h>

namespace {

constexpr int kSeq = 2048;
constexpr int kD = 640;
constexpr int kGrid = 132;
constexpr int kThreads = 384;

constexpr uint32_t kBlob = 20480;
constexpr uint32_t kFold = 19456;
constexpr uint32_t kPair = 5152;
constexpr uint32_t kHalf = 20576;
constexpr uint32_t kKv = 16384;
constexpr uint32_t kPrepW = 24576, kPrepPhi = 6400;

constexpr uint32_t SB = 1024;
constexpr uint32_t BARS = SB;
constexpr uint32_t A_ONES = SB + 640;
constexpr uint32_t A_PHI = SB + 6976;
constexpr uint32_t A_X = A_PHI + 2 * kHalf;
constexpr uint32_t A_RING = A_X + 81920;
constexpr uint32_t A_KV0 = A_X, A_KV1 = A_RING - 2 * kKv;
constexpr uint32_t B_RING = SB + 1024;
constexpr uint32_t B_SLOT = 36864;
constexpr uint32_t B_STG = B_RING + 5 * B_SLOT;
constexpr uint32_t B_ZERO = B_STG + 40960;
constexpr uint32_t B_CONST = B_ZERO + 2048;
constexpr uint32_t kSmem = 232448;

constexpr uint32_t BAR_FULL = BARS, BAR_EMPTY = BARS + 40, BAR_TOK = BARS + 80, BAR_STG = BARS + 96, BAR_V = BARS + 104,
                   BAR_O = BARS + 112, BAR_KV0 = BARS + 128, BAR_P = BARS + 136, BAR_KVR = BARS + 144, BAR_P1 = BARS + 160,
                   BAR_X = BARS + 168, BAR_FREE = BARS + 248, BAR_RED = BARS + 264, BAR_QD = BARS + 280, BAR_QF = BARS + 288,
                   BAR_QS = BARS + 304, BAR_DONE = BARS + 336, BAR_DUMMY = BARS + 344, BAR_PREP = BARS + 352,
                   BAR_STG1 = BARS + 360, BAR_W = BARS + 368, BAR_END = BARS + 408;
enum { C_W = 0, C_KV = 2 * 32, C_H = 6 * 32, C_O = 32 * 32 };

struct Scratch {
  unsigned char kv[4 * 2 * kKv];
  unsigned long long fin[13 * 640];
  unsigned cnt[160 * 32];
  unsigned ep[136 * 32];
  unsigned char w[120 * kBlob];
  unsigned char ox[128 * kBlob];
  unsigned char h[260 * kBlob];
};
__device__ __align__(1024) Scratch g_scratch;

struct Params {
  Scratch* s;
  float* out;
  const __nv_bfloat16 *wphi, *cre_p, *cim_p, *lre, *lim, *logdt, *dskip;
  int one;
  CUtensorMap xa, wv, wp, xb, bre, bim, xbl, cre, cim, wop;
};

template <int TB>
__device__ __forceinline__ void wgmma_n128(float* d, uint64_t da, uint64_t db, int sc) {
  asm volatile("{ .reg .pred p; setp.ne.b32 p, %66, 0;\n"
    "wgmma.mma_async.sync.aligned.m64n128k16.f32.bf16.bf16 {%0,%1,%2,%3,%4,%5,%6,%7,%8,%9,%10,%11,%12,%13,%14,%15,%16,%17,%18,%19,%20,%21,%22,%23,%24,%25,%26,%27,%28,%29,%30,%31,%32,%33,%34,%35,%36,%37,%38,%39,%40,%41,%42,%43,%44,%45,%46,%47,%48,%49,%50,%51,%52,%53,%54,%55,%56,%57,%58,%59,%60,%61,%62,%63}, %64, %65, p, 1, 1, 0, %67; }"
    : "+f"(d[0]),"+f"(d[1]),"+f"(d[2]),"+f"(d[3]),"+f"(d[4]),"+f"(d[5]),"+f"(d[6]),"+f"(d[7]),"+f"(d[8]),"+f"(d[9]),"+f"(d[10]),"+f"(d[11]),"+f"(d[12]),"+f"(d[13]),"+f"(d[14]),"+f"(d[15]),"+f"(d[16]),"+f"(d[17]),"+f"(d[18]),"+f"(d[19]),"+f"(d[20]),"+f"(d[21]),"+f"(d[22]),"+f"(d[23]),"+f"(d[24]),"+f"(d[25]),"+f"(d[26]),"+f"(d[27]),"+f"(d[28]),"+f"(d[29]),"+f"(d[30]),"+f"(d[31]),"+f"(d[32]),"+f"(d[33]),"+f"(d[34]),"+f"(d[35]),"+f"(d[36]),"+f"(d[37]),"+f"(d[38]),"+f"(d[39]),"+f"(d[40]),"+f"(d[41]),"+f"(d[42]),"+f"(d[43]),"+f"(d[44]),"+f"(d[45]),"+f"(d[46]),"+f"(d[47]),"+f"(d[48]),"+f"(d[49]),"+f"(d[50]),"+f"(d[51]),"+f"(d[52]),"+f"(d[53]),"+f"(d[54]),"+f"(d[55]),"+f"(d[56]),"+f"(d[57]),"+f"(d[58]),"+f"(d[59]),"+f"(d[60]),"+f"(d[61]),"+f"(d[62]),"+f"(d[63])
    : "l"(da), "l"(db), "r"(sc), "n"(TB));
}
template <int TB>
__device__ __forceinline__ void wgmma_n192(float* d, uint64_t da, uint64_t db, int sc) {
  asm volatile("{ .reg .pred p; setp.ne.b32 p, %98, 0;\n"
    "wgmma.mma_async.sync.aligned.m64n192k16.f32.bf16.bf16 {%0,%1,%2,%3,%4,%5,%6,%7,%8,%9,%10,%11,%12,%13,%14,%15,%16,%17,%18,%19,%20,%21,%22,%23,%24,%25,%26,%27,%28,%29,%30,%31,%32,%33,%34,%35,%36,%37,%38,%39,%40,%41,%42,%43,%44,%45,%46,%47,%48,%49,%50,%51,%52,%53,%54,%55,%56,%57,%58,%59,%60,%61,%62,%63,%64,%65,%66,%67,%68,%69,%70,%71,%72,%73,%74,%75,%76,%77,%78,%79,%80,%81,%82,%83,%84,%85,%86,%87,%88,%89,%90,%91,%92,%93,%94,%95}, %96, %97, p, 1, 1, 0, %99; }"
    : "+f"(d[0]),"+f"(d[1]),"+f"(d[2]),"+f"(d[3]),"+f"(d[4]),"+f"(d[5]),"+f"(d[6]),"+f"(d[7]),"+f"(d[8]),"+f"(d[9]),"+f"(d[10]),"+f"(d[11]),"+f"(d[12]),"+f"(d[13]),"+f"(d[14]),"+f"(d[15]),"+f"(d[16]),"+f"(d[17]),"+f"(d[18]),"+f"(d[19]),"+f"(d[20]),"+f"(d[21]),"+f"(d[22]),"+f"(d[23]),"+f"(d[24]),"+f"(d[25]),"+f"(d[26]),"+f"(d[27]),"+f"(d[28]),"+f"(d[29]),"+f"(d[30]),"+f"(d[31]),"+f"(d[32]),"+f"(d[33]),"+f"(d[34]),"+f"(d[35]),"+f"(d[36]),"+f"(d[37]),"+f"(d[38]),"+f"(d[39]),"+f"(d[40]),"+f"(d[41]),"+f"(d[42]),"+f"(d[43]),"+f"(d[44]),"+f"(d[45]),"+f"(d[46]),"+f"(d[47]),"+f"(d[48]),"+f"(d[49]),"+f"(d[50]),"+f"(d[51]),"+f"(d[52]),"+f"(d[53]),"+f"(d[54]),"+f"(d[55]),"+f"(d[56]),"+f"(d[57]),"+f"(d[58]),"+f"(d[59]),"+f"(d[60]),"+f"(d[61]),"+f"(d[62]),"+f"(d[63]),"+f"(d[64]),"+f"(d[65]),"+f"(d[66]),"+f"(d[67]),"+f"(d[68]),"+f"(d[69]),"+f"(d[70]),"+f"(d[71]),"+f"(d[72]),"+f"(d[73]),"+f"(d[74]),"+f"(d[75]),"+f"(d[76]),"+f"(d[77]),"+f"(d[78]),"+f"(d[79]),"+f"(d[80]),"+f"(d[81]),"+f"(d[82]),"+f"(d[83]),"+f"(d[84]),"+f"(d[85]),"+f"(d[86]),"+f"(d[87]),"+f"(d[88]),"+f"(d[89]),"+f"(d[90]),"+f"(d[91]),"+f"(d[92]),"+f"(d[93]),"+f"(d[94]),"+f"(d[95])
    : "l"(da), "l"(db), "r"(sc), "n"(TB));
}

__device__ __forceinline__ void wg_fence() { asm volatile("wgmma.fence.sync.aligned;" ::: "memory"); }
__device__ __forceinline__ void wg_commit() { asm volatile("wgmma.commit_group.sync.aligned;" ::: "memory"); }
template <int N> __device__ __forceinline__ void wg_wait() { asm volatile("wgmma.wait_group.sync.aligned %0;" ::"n"(N) : "memory"); }
template <int N> __device__ __forceinline__ void reg_fence(float* d) {
#pragma unroll
  for (int i = 0; i < N; i++) asm volatile("" : "+f"(d[i])::"memory");
}
template <int N> __device__ __forceinline__ void reg_define(float* d) {
#pragma unroll
  for (int i = 0; i < N; i++) asm volatile("" : "=f"(d[i]));
}
__host__ __device__ constexpr uint32_t desc_lo(uint32_t addr, uint32_t lbo) { return (addr >> 4) | ((lbo >> 4) << 16); }
constexpr uint32_t kHiSw128 = (1024 >> 4) | (1u << 30);
constexpr uint32_t kHiPlain = 128 >> 4;
__device__ __forceinline__ uint64_t mkdesc(uint32_t lo, uint32_t hi) { return ((uint64_t)hi << 32) | lo; }
__device__ __forceinline__ int uniform(int v) { return __shfl_sync(~0u, v, 0); }

__device__ __forceinline__ void a_mainloop152(float* d, uint32_t tok) {
  asm volatile(
    "{ .reg .pred pe, pw, pz, pt; .reg .b32 hb, t, u; .reg .b64 dA, dB;\n"
    "mov.b32 hb, %80; mov.u32 t, %%laneid; setp.lt.u32 pe, t, 2; setp.ne.b32 pz, 0, 0; setp.eq.b32 pt, 0, 0;\n"
    "mov.b32 t, %78+0;\n"
    "W0: mbarrier.try_wait.parity.shared::cta.b64 pw, [t], 0, 100000;\n"
    "@!pw bra W0;\n"
    "wgmma.fence.sync.aligned;\n"
    "mov.b32 t, %76+0; mov.b32 u, %77+0;\n"
    "mov.b64 dA, {t, hb}; mov.b64 dB, {u, hb};\n"
    "wgmma.mma_async.sync.aligned.m64n152k16.f32.bf16.bf16 {%0,%1,%2,%3,%4,%5,%6,%7,%8,%9,%10,%11,%12,%13,%14,%15,%16,%17,%18,%19,%20,%21,%22,%23,%24,%25,%26,%27,%28,%29,%30,%31,%32,%33,%34,%35,%36,%37,%38,%39,%40,%41,%42,%43,%44,%45,%46,%47,%48,%49,%50,%51,%52,%53,%54,%55,%56,%57,%58,%59,%60,%61,%62,%63,%64,%65,%66,%67,%68,%69,%70,%71,%72,%73,%74,%75}, dA, dB, pz, 1, 1, 0, 0;\n"
    "mov.b32 t, %76+2; mov.b32 u, %77+2;\n"
    "mov.b64 dA, {t, hb}; mov.b64 dB, {u, hb};\n"
    "wgmma.mma_async.sync.aligned.m64n152k16.f32.bf16.bf16 {%0,%1,%2,%3,%4,%5,%6,%7,%8,%9,%10,%11,%12,%13,%14,%15,%16,%17,%18,%19,%20,%21,%22,%23,%24,%25,%26,%27,%28,%29,%30,%31,%32,%33,%34,%35,%36,%37,%38,%39,%40,%41,%42,%43,%44,%45,%46,%47,%48,%49,%50,%51,%52,%53,%54,%55,%56,%57,%58,%59,%60,%61,%62,%63,%64,%65,%66,%67,%68,%69,%70,%71,%72,%73,%74,%75}, dA, dB, pt, 1, 1, 0, 0;\n"
    "mov.b32 t, %76+4; mov.b32 u, %77+4;\n"
    "mov.b64 dA, {t, hb}; mov.b64 dB, {u, hb};\n"
    "wgmma.mma_async.sync.aligned.m64n152k16.f32.bf16.bf16 {%0,%1,%2,%3,%4,%5,%6,%7,%8,%9,%10,%11,%12,%13,%14,%15,%16,%17,%18,%19,%20,%21,%22,%23,%24,%25,%26,%27,%28,%29,%30,%31,%32,%33,%34,%35,%36,%37,%38,%39,%40,%41,%42,%43,%44,%45,%46,%47,%48,%49,%50,%51,%52,%53,%54,%55,%56,%57,%58,%59,%60,%61,%62,%63,%64,%65,%66,%67,%68,%69,%70,%71,%72,%73,%74,%75}, dA, dB, pt, 1, 1, 0, 0;\n"
    "mov.b32 t, %76+6; mov.b32 u, %77+6;\n"
    "mov.b64 dA, {t, hb}; mov.b64 dB, {u, hb};\n"
    "wgmma.mma_async.sync.aligned.m64n152k16.f32.bf16.bf16 {%0,%1,%2,%3,%4,%5,%6,%7,%8,%9,%10,%11,%12,%13,%14,%15,%16,%17,%18,%19,%20,%21,%22,%23,%24,%25,%26,%27,%28,%29,%30,%31,%32,%33,%34,%35,%36,%37,%38,%39,%40,%41,%42,%43,%44,%45,%46,%47,%48,%49,%50,%51,%52,%53,%54,%55,%56,%57,%58,%59,%60,%61,%62,%63,%64,%65,%66,%67,%68,%69,%70,%71,%72,%73,%74,%75}, dA, dB, pt, 1, 1, 0, 0;\n"
    "wgmma.commit_group.sync.aligned;\n"
    "mov.b32 t, %78+8;\n"
    "W1: mbarrier.try_wait.parity.shared::cta.b64 pw, [t], 0, 100000;\n"
    "@!pw bra W1;\n"
    "wgmma.fence.sync.aligned;\n"
    "mov.b32 t, %76+512; mov.b32 u, %77+1280;\n"
    "mov.b64 dA, {t, hb}; mov.b64 dB, {u, hb};\n"
    "wgmma.mma_async.sync.aligned.m64n152k16.f32.bf16.bf16 {%0,%1,%2,%3,%4,%5,%6,%7,%8,%9,%10,%11,%12,%13,%14,%15,%16,%17,%18,%19,%20,%21,%22,%23,%24,%25,%26,%27,%28,%29,%30,%31,%32,%33,%34,%35,%36,%37,%38,%39,%40,%41,%42,%43,%44,%45,%46,%47,%48,%49,%50,%51,%52,%53,%54,%55,%56,%57,%58,%59,%60,%61,%62,%63,%64,%65,%66,%67,%68,%69,%70,%71,%72,%73,%74,%75}, dA, dB, pt, 1, 1, 0, 0;\n"
    "mov.b32 t, %76+514; mov.b32 u, %77+1282;\n"
    "mov.b64 dA, {t, hb}; mov.b64 dB, {u, hb};\n"
    "wgmma.mma_async.sync.aligned.m64n152k16.f32.bf16.bf16 {%0,%1,%2,%3,%4,%5,%6,%7,%8,%9,%10,%11,%12,%13,%14,%15,%16,%17,%18,%19,%20,%21,%22,%23,%24,%25,%26,%27,%28,%29,%30,%31,%32,%33,%34,%35,%36,%37,%38,%39,%40,%41,%42,%43,%44,%45,%46,%47,%48,%49,%50,%51,%52,%53,%54,%55,%56,%57,%58,%59,%60,%61,%62,%63,%64,%65,%66,%67,%68,%69,%70,%71,%72,%73,%74,%75}, dA, dB, pt, 1, 1, 0, 0;\n"
    "wgmma.commit_group.sync.aligned;\n"
    "wgmma.wait_group.sync.aligned 1;\n"
    "mov.b32 t, %79+0;\n"
    "@pe mbarrier.arrive.shared::cta.b64 _, [t];\n"
    "mov.b32 t, %76+516; mov.b32 u, %77+1284;\n"
    "mov.b64 dA, {t, hb}; mov.b64 dB, {u, hb};\n"
    "wgmma.mma_async.sync.aligned.m64n152k16.f32.bf16.bf16 {%0,%1,%2,%3,%4,%5,%6,%7,%8,%9,%10,%11,%12,%13,%14,%15,%16,%17,%18,%19,%20,%21,%22,%23,%24,%25,%26,%27,%28,%29,%30,%31,%32,%33,%34,%35,%36,%37,%38,%39,%40,%41,%42,%43,%44,%45,%46,%47,%48,%49,%50,%51,%52,%53,%54,%55,%56,%57,%58,%59,%60,%61,%62,%63,%64,%65,%66,%67,%68,%69,%70,%71,%72,%73,%74,%75}, dA, dB, pt, 1, 1, 0, 0;\n"
    "mov.b32 t, %76+518; mov.b32 u, %77+1286;\n"
    "mov.b64 dA, {t, hb}; mov.b64 dB, {u, hb};\n"
    "wgmma.mma_async.sync.aligned.m64n152k16.f32.bf16.bf16 {%0,%1,%2,%3,%4,%5,%6,%7,%8,%9,%10,%11,%12,%13,%14,%15,%16,%17,%18,%19,%20,%21,%22,%23,%24,%25,%26,%27,%28,%29,%30,%31,%32,%33,%34,%35,%36,%37,%38,%39,%40,%41,%42,%43,%44,%45,%46,%47,%48,%49,%50,%51,%52,%53,%54,%55,%56,%57,%58,%59,%60,%61,%62,%63,%64,%65,%66,%67,%68,%69,%70,%71,%72,%73,%74,%75}, dA, dB, pt, 1, 1, 0, 0;\n"
    "wgmma.commit_group.sync.aligned;\n"
    "mov.b32 t, %78+16;\n"
    "W2: mbarrier.try_wait.parity.shared::cta.b64 pw, [t], 0, 100000;\n"
    "@!pw bra W2;\n"
    "wgmma.fence.sync.aligned;\n"
    "mov.b32 t, %76+1024; mov.b32 u, %77+2560;\n"
    "mov.b64 dA, {t, hb}; mov.b64 dB, {u, hb};\n"
    "wgmma.mma_async.sync.aligned.m64n152k16.f32.bf16.bf16 {%0,%1,%2,%3,%4,%5,%6,%7,%8,%9,%10,%11,%12,%13,%14,%15,%16,%17,%18,%19,%20,%21,%22,%23,%24,%25,%26,%27,%28,%29,%30,%31,%32,%33,%34,%35,%36,%37,%38,%39,%40,%41,%42,%43,%44,%45,%46,%47,%48,%49,%50,%51,%52,%53,%54,%55,%56,%57,%58,%59,%60,%61,%62,%63,%64,%65,%66,%67,%68,%69,%70,%71,%72,%73,%74,%75}, dA, dB, pt, 1, 1, 0, 0;\n"
    "mov.b32 t, %76+1026; mov.b32 u, %77+2562;\n"
    "mov.b64 dA, {t, hb}; mov.b64 dB, {u, hb};\n"
    "wgmma.mma_async.sync.aligned.m64n152k16.f32.bf16.bf16 {%0,%1,%2,%3,%4,%5,%6,%7,%8,%9,%10,%11,%12,%13,%14,%15,%16,%17,%18,%19,%20,%21,%22,%23,%24,%25,%26,%27,%28,%29,%30,%31,%32,%33,%34,%35,%36,%37,%38,%39,%40,%41,%42,%43,%44,%45,%46,%47,%48,%49,%50,%51,%52,%53,%54,%55,%56,%57,%58,%59,%60,%61,%62,%63,%64,%65,%66,%67,%68,%69,%70,%71,%72,%73,%74,%75}, dA, dB, pt, 1, 1, 0, 0;\n"
    "wgmma.commit_group.sync.aligned;\n"
    "wgmma.wait_group.sync.aligned 1;\n"
    "mov.b32 t, %79+8;\n"
    "@pe mbarrier.arrive.shared::cta.b64 _, [t];\n"
    "mov.b32 t, %76+1028; mov.b32 u, %77+2564;\n"
    "mov.b64 dA, {t, hb}; mov.b64 dB, {u, hb};\n"
    "wgmma.mma_async.sync.aligned.m64n152k16.f32.bf16.bf16 {%0,%1,%2,%3,%4,%5,%6,%7,%8,%9,%10,%11,%12,%13,%14,%15,%16,%17,%18,%19,%20,%21,%22,%23,%24,%25,%26,%27,%28,%29,%30,%31,%32,%33,%34,%35,%36,%37,%38,%39,%40,%41,%42,%43,%44,%45,%46,%47,%48,%49,%50,%51,%52,%53,%54,%55,%56,%57,%58,%59,%60,%61,%62,%63,%64,%65,%66,%67,%68,%69,%70,%71,%72,%73,%74,%75}, dA, dB, pt, 1, 1, 0, 0;\n"
    "mov.b32 t, %76+1030; mov.b32 u, %77+2566;\n"
    "mov.b64 dA, {t, hb}; mov.b64 dB, {u, hb};\n"
    "wgmma.mma_async.sync.aligned.m64n152k16.f32.bf16.bf16 {%0,%1,%2,%3,%4,%5,%6,%7,%8,%9,%10,%11,%12,%13,%14,%15,%16,%17,%18,%19,%20,%21,%22,%23,%24,%25,%26,%27,%28,%29,%30,%31,%32,%33,%34,%35,%36,%37,%38,%39,%40,%41,%42,%43,%44,%45,%46,%47,%48,%49,%50,%51,%52,%53,%54,%55,%56,%57,%58,%59,%60,%61,%62,%63,%64,%65,%66,%67,%68,%69,%70,%71,%72,%73,%74,%75}, dA, dB, pt, 1, 1, 0, 0;\n"
    "wgmma.commit_group.sync.aligned;\n"
    "mov.b32 t, %78+24;\n"
    "W3: mbarrier.try_wait.parity.shared::cta.b64 pw, [t], 0, 100000;\n"
    "@!pw bra W3;\n"
    "wgmma.fence.sync.aligned;\n"
    "mov.b32 t, %76+1536; mov.b32 u, %77+3840;\n"
    "mov.b64 dA, {t, hb}; mov.b64 dB, {u, hb};\n"
    "wgmma.mma_async.sync.aligned.m64n152k16.f32.bf16.bf16 {%0,%1,%2,%3,%4,%5,%6,%7,%8,%9,%10,%11,%12,%13,%14,%15,%16,%17,%18,%19,%20,%21,%22,%23,%24,%25,%26,%27,%28,%29,%30,%31,%32,%33,%34,%35,%36,%37,%38,%39,%40,%41,%42,%43,%44,%45,%46,%47,%48,%49,%50,%51,%52,%53,%54,%55,%56,%57,%58,%59,%60,%61,%62,%63,%64,%65,%66,%67,%68,%69,%70,%71,%72,%73,%74,%75}, dA, dB, pt, 1, 1, 0, 0;\n"
    "mov.b32 t, %76+1538; mov.b32 u, %77+3842;\n"
    "mov.b64 dA, {t, hb}; mov.b64 dB, {u, hb};\n"
    "wgmma.mma_async.sync.aligned.m64n152k16.f32.bf16.bf16 {%0,%1,%2,%3,%4,%5,%6,%7,%8,%9,%10,%11,%12,%13,%14,%15,%16,%17,%18,%19,%20,%21,%22,%23,%24,%25,%26,%27,%28,%29,%30,%31,%32,%33,%34,%35,%36,%37,%38,%39,%40,%41,%42,%43,%44,%45,%46,%47,%48,%49,%50,%51,%52,%53,%54,%55,%56,%57,%58,%59,%60,%61,%62,%63,%64,%65,%66,%67,%68,%69,%70,%71,%72,%73,%74,%75}, dA, dB, pt, 1, 1, 0, 0;\n"
    "wgmma.commit_group.sync.aligned;\n"
    "wgmma.wait_group.sync.aligned 1;\n"
    "mov.b32 t, %79+16;\n"
    "@pe mbarrier.arrive.shared::cta.b64 _, [t];\n"
    "mov.b32 t, %76+1540; mov.b32 u, %77+3844;\n"
    "mov.b64 dA, {t, hb}; mov.b64 dB, {u, hb};\n"
    "wgmma.mma_async.sync.aligned.m64n152k16.f32.bf16.bf16 {%0,%1,%2,%3,%4,%5,%6,%7,%8,%9,%10,%11,%12,%13,%14,%15,%16,%17,%18,%19,%20,%21,%22,%23,%24,%25,%26,%27,%28,%29,%30,%31,%32,%33,%34,%35,%36,%37,%38,%39,%40,%41,%42,%43,%44,%45,%46,%47,%48,%49,%50,%51,%52,%53,%54,%55,%56,%57,%58,%59,%60,%61,%62,%63,%64,%65,%66,%67,%68,%69,%70,%71,%72,%73,%74,%75}, dA, dB, pt, 1, 1, 0, 0;\n"
    "mov.b32 t, %76+1542; mov.b32 u, %77+3846;\n"
    "mov.b64 dA, {t, hb}; mov.b64 dB, {u, hb};\n"
    "wgmma.mma_async.sync.aligned.m64n152k16.f32.bf16.bf16 {%0,%1,%2,%3,%4,%5,%6,%7,%8,%9,%10,%11,%12,%13,%14,%15,%16,%17,%18,%19,%20,%21,%22,%23,%24,%25,%26,%27,%28,%29,%30,%31,%32,%33,%34,%35,%36,%37,%38,%39,%40,%41,%42,%43,%44,%45,%46,%47,%48,%49,%50,%51,%52,%53,%54,%55,%56,%57,%58,%59,%60,%61,%62,%63,%64,%65,%66,%67,%68,%69,%70,%71,%72,%73,%74,%75}, dA, dB, pt, 1, 1, 0, 0;\n"
    "wgmma.commit_group.sync.aligned;\n"
    "mov.b32 t, %78+32;\n"
    "W4: mbarrier.try_wait.parity.shared::cta.b64 pw, [t], 0, 100000;\n"
    "@!pw bra W4;\n"
    "wgmma.fence.sync.aligned;\n"
    "mov.b32 t, %76+2048; mov.b32 u, %77+5120;\n"
    "mov.b64 dA, {t, hb}; mov.b64 dB, {u, hb};\n"
    "wgmma.mma_async.sync.aligned.m64n152k16.f32.bf16.bf16 {%0,%1,%2,%3,%4,%5,%6,%7,%8,%9,%10,%11,%12,%13,%14,%15,%16,%17,%18,%19,%20,%21,%22,%23,%24,%25,%26,%27,%28,%29,%30,%31,%32,%33,%34,%35,%36,%37,%38,%39,%40,%41,%42,%43,%44,%45,%46,%47,%48,%49,%50,%51,%52,%53,%54,%55,%56,%57,%58,%59,%60,%61,%62,%63,%64,%65,%66,%67,%68,%69,%70,%71,%72,%73,%74,%75}, dA, dB, pt, 1, 1, 0, 0;\n"
    "mov.b32 t, %76+2050; mov.b32 u, %77+5122;\n"
    "mov.b64 dA, {t, hb}; mov.b64 dB, {u, hb};\n"
    "wgmma.mma_async.sync.aligned.m64n152k16.f32.bf16.bf16 {%0,%1,%2,%3,%4,%5,%6,%7,%8,%9,%10,%11,%12,%13,%14,%15,%16,%17,%18,%19,%20,%21,%22,%23,%24,%25,%26,%27,%28,%29,%30,%31,%32,%33,%34,%35,%36,%37,%38,%39,%40,%41,%42,%43,%44,%45,%46,%47,%48,%49,%50,%51,%52,%53,%54,%55,%56,%57,%58,%59,%60,%61,%62,%63,%64,%65,%66,%67,%68,%69,%70,%71,%72,%73,%74,%75}, dA, dB, pt, 1, 1, 0, 0;\n"
    "wgmma.commit_group.sync.aligned;\n"
    "wgmma.wait_group.sync.aligned 1;\n"
    "mov.b32 t, %79+24;\n"
    "@pe mbarrier.arrive.shared::cta.b64 _, [t];\n"
    "mov.b32 t, %76+2052; mov.b32 u, %77+5124;\n"
    "mov.b64 dA, {t, hb}; mov.b64 dB, {u, hb};\n"
    "wgmma.mma_async.sync.aligned.m64n152k16.f32.bf16.bf16 {%0,%1,%2,%3,%4,%5,%6,%7,%8,%9,%10,%11,%12,%13,%14,%15,%16,%17,%18,%19,%20,%21,%22,%23,%24,%25,%26,%27,%28,%29,%30,%31,%32,%33,%34,%35,%36,%37,%38,%39,%40,%41,%42,%43,%44,%45,%46,%47,%48,%49,%50,%51,%52,%53,%54,%55,%56,%57,%58,%59,%60,%61,%62,%63,%64,%65,%66,%67,%68,%69,%70,%71,%72,%73,%74,%75}, dA, dB, pt, 1, 1, 0, 0;\n"
    "mov.b32 t, %76+2054; mov.b32 u, %77+5126;\n"
    "mov.b64 dA, {t, hb}; mov.b64 dB, {u, hb};\n"
    "wgmma.mma_async.sync.aligned.m64n152k16.f32.bf16.bf16 {%0,%1,%2,%3,%4,%5,%6,%7,%8,%9,%10,%11,%12,%13,%14,%15,%16,%17,%18,%19,%20,%21,%22,%23,%24,%25,%26,%27,%28,%29,%30,%31,%32,%33,%34,%35,%36,%37,%38,%39,%40,%41,%42,%43,%44,%45,%46,%47,%48,%49,%50,%51,%52,%53,%54,%55,%56,%57,%58,%59,%60,%61,%62,%63,%64,%65,%66,%67,%68,%69,%70,%71,%72,%73,%74,%75}, dA, dB, pt, 1, 1, 0, 0;\n"
    "wgmma.commit_group.sync.aligned;\n"
    "mov.b32 t, %78+0;\n"
    "W5: mbarrier.try_wait.parity.shared::cta.b64 pw, [t], 1, 100000;\n"
    "@!pw bra W5;\n"
    "wgmma.fence.sync.aligned;\n"
    "mov.b32 t, %76+2560; mov.b32 u, %77+0;\n"
    "mov.b64 dA, {t, hb}; mov.b64 dB, {u, hb};\n"
    "wgmma.mma_async.sync.aligned.m64n152k16.f32.bf16.bf16 {%0,%1,%2,%3,%4,%5,%6,%7,%8,%9,%10,%11,%12,%13,%14,%15,%16,%17,%18,%19,%20,%21,%22,%23,%24,%25,%26,%27,%28,%29,%30,%31,%32,%33,%34,%35,%36,%37,%38,%39,%40,%41,%42,%43,%44,%45,%46,%47,%48,%49,%50,%51,%52,%53,%54,%55,%56,%57,%58,%59,%60,%61,%62,%63,%64,%65,%66,%67,%68,%69,%70,%71,%72,%73,%74,%75}, dA, dB, pt, 1, 1, 0, 0;\n"
    "mov.b32 t, %76+2562; mov.b32 u, %77+2;\n"
    "mov.b64 dA, {t, hb}; mov.b64 dB, {u, hb};\n"
    "wgmma.mma_async.sync.aligned.m64n152k16.f32.bf16.bf16 {%0,%1,%2,%3,%4,%5,%6,%7,%8,%9,%10,%11,%12,%13,%14,%15,%16,%17,%18,%19,%20,%21,%22,%23,%24,%25,%26,%27,%28,%29,%30,%31,%32,%33,%34,%35,%36,%37,%38,%39,%40,%41,%42,%43,%44,%45,%46,%47,%48,%49,%50,%51,%52,%53,%54,%55,%56,%57,%58,%59,%60,%61,%62,%63,%64,%65,%66,%67,%68,%69,%70,%71,%72,%73,%74,%75}, dA, dB, pt, 1, 1, 0, 0;\n"
    "wgmma.commit_group.sync.aligned;\n"
    "wgmma.wait_group.sync.aligned 1;\n"
    "mov.b32 t, %79+32;\n"
    "@pe mbarrier.arrive.shared::cta.b64 _, [t];\n"
    "mov.b32 t, %76+2564; mov.b32 u, %77+4;\n"
    "mov.b64 dA, {t, hb}; mov.b64 dB, {u, hb};\n"
    "wgmma.mma_async.sync.aligned.m64n152k16.f32.bf16.bf16 {%0,%1,%2,%3,%4,%5,%6,%7,%8,%9,%10,%11,%12,%13,%14,%15,%16,%17,%18,%19,%20,%21,%22,%23,%24,%25,%26,%27,%28,%29,%30,%31,%32,%33,%34,%35,%36,%37,%38,%39,%40,%41,%42,%43,%44,%45,%46,%47,%48,%49,%50,%51,%52,%53,%54,%55,%56,%57,%58,%59,%60,%61,%62,%63,%64,%65,%66,%67,%68,%69,%70,%71,%72,%73,%74,%75}, dA, dB, pt, 1, 1, 0, 0;\n"
    "mov.b32 t, %76+2566; mov.b32 u, %77+6;\n"
    "mov.b64 dA, {t, hb}; mov.b64 dB, {u, hb};\n"
    "wgmma.mma_async.sync.aligned.m64n152k16.f32.bf16.bf16 {%0,%1,%2,%3,%4,%5,%6,%7,%8,%9,%10,%11,%12,%13,%14,%15,%16,%17,%18,%19,%20,%21,%22,%23,%24,%25,%26,%27,%28,%29,%30,%31,%32,%33,%34,%35,%36,%37,%38,%39,%40,%41,%42,%43,%44,%45,%46,%47,%48,%49,%50,%51,%52,%53,%54,%55,%56,%57,%58,%59,%60,%61,%62,%63,%64,%65,%66,%67,%68,%69,%70,%71,%72,%73,%74,%75}, dA, dB, pt, 1, 1, 0, 0;\n"
    "wgmma.commit_group.sync.aligned;\n"
    "mov.b32 t, %78+8;\n"
    "W6: mbarrier.try_wait.parity.shared::cta.b64 pw, [t], 1, 100000;\n"
    "@!pw bra W6;\n"
    "wgmma.fence.sync.aligned;\n"
    "mov.b32 t, %76+3072; mov.b32 u, %77+1280;\n"
    "mov.b64 dA, {t, hb}; mov.b64 dB, {u, hb};\n"
    "wgmma.mma_async.sync.aligned.m64n152k16.f32.bf16.bf16 {%0,%1,%2,%3,%4,%5,%6,%7,%8,%9,%10,%11,%12,%13,%14,%15,%16,%17,%18,%19,%20,%21,%22,%23,%24,%25,%26,%27,%28,%29,%30,%31,%32,%33,%34,%35,%36,%37,%38,%39,%40,%41,%42,%43,%44,%45,%46,%47,%48,%49,%50,%51,%52,%53,%54,%55,%56,%57,%58,%59,%60,%61,%62,%63,%64,%65,%66,%67,%68,%69,%70,%71,%72,%73,%74,%75}, dA, dB, pt, 1, 1, 0, 0;\n"
    "mov.b32 t, %76+3074; mov.b32 u, %77+1282;\n"
    "mov.b64 dA, {t, hb}; mov.b64 dB, {u, hb};\n"
    "wgmma.mma_async.sync.aligned.m64n152k16.f32.bf16.bf16 {%0,%1,%2,%3,%4,%5,%6,%7,%8,%9,%10,%11,%12,%13,%14,%15,%16,%17,%18,%19,%20,%21,%22,%23,%24,%25,%26,%27,%28,%29,%30,%31,%32,%33,%34,%35,%36,%37,%38,%39,%40,%41,%42,%43,%44,%45,%46,%47,%48,%49,%50,%51,%52,%53,%54,%55,%56,%57,%58,%59,%60,%61,%62,%63,%64,%65,%66,%67,%68,%69,%70,%71,%72,%73,%74,%75}, dA, dB, pt, 1, 1, 0, 0;\n"
    "wgmma.commit_group.sync.aligned;\n"
    "wgmma.wait_group.sync.aligned 1;\n"
    "mov.b32 t, %79+0;\n"
    "@pe mbarrier.arrive.shared::cta.b64 _, [t];\n"
    "mov.b32 t, %76+3076; mov.b32 u, %77+1284;\n"
    "mov.b64 dA, {t, hb}; mov.b64 dB, {u, hb};\n"
    "wgmma.mma_async.sync.aligned.m64n152k16.f32.bf16.bf16 {%0,%1,%2,%3,%4,%5,%6,%7,%8,%9,%10,%11,%12,%13,%14,%15,%16,%17,%18,%19,%20,%21,%22,%23,%24,%25,%26,%27,%28,%29,%30,%31,%32,%33,%34,%35,%36,%37,%38,%39,%40,%41,%42,%43,%44,%45,%46,%47,%48,%49,%50,%51,%52,%53,%54,%55,%56,%57,%58,%59,%60,%61,%62,%63,%64,%65,%66,%67,%68,%69,%70,%71,%72,%73,%74,%75}, dA, dB, pt, 1, 1, 0, 0;\n"
    "mov.b32 t, %76+3078; mov.b32 u, %77+1286;\n"
    "mov.b64 dA, {t, hb}; mov.b64 dB, {u, hb};\n"
    "wgmma.mma_async.sync.aligned.m64n152k16.f32.bf16.bf16 {%0,%1,%2,%3,%4,%5,%6,%7,%8,%9,%10,%11,%12,%13,%14,%15,%16,%17,%18,%19,%20,%21,%22,%23,%24,%25,%26,%27,%28,%29,%30,%31,%32,%33,%34,%35,%36,%37,%38,%39,%40,%41,%42,%43,%44,%45,%46,%47,%48,%49,%50,%51,%52,%53,%54,%55,%56,%57,%58,%59,%60,%61,%62,%63,%64,%65,%66,%67,%68,%69,%70,%71,%72,%73,%74,%75}, dA, dB, pt, 1, 1, 0, 0;\n"
    "wgmma.commit_group.sync.aligned;\n"
    "mov.b32 t, %78+16;\n"
    "W7: mbarrier.try_wait.parity.shared::cta.b64 pw, [t], 1, 100000;\n"
    "@!pw bra W7;\n"
    "wgmma.fence.sync.aligned;\n"
    "mov.b32 t, %76+3584; mov.b32 u, %77+2560;\n"
    "mov.b64 dA, {t, hb}; mov.b64 dB, {u, hb};\n"
    "wgmma.mma_async.sync.aligned.m64n152k16.f32.bf16.bf16 {%0,%1,%2,%3,%4,%5,%6,%7,%8,%9,%10,%11,%12,%13,%14,%15,%16,%17,%18,%19,%20,%21,%22,%23,%24,%25,%26,%27,%28,%29,%30,%31,%32,%33,%34,%35,%36,%37,%38,%39,%40,%41,%42,%43,%44,%45,%46,%47,%48,%49,%50,%51,%52,%53,%54,%55,%56,%57,%58,%59,%60,%61,%62,%63,%64,%65,%66,%67,%68,%69,%70,%71,%72,%73,%74,%75}, dA, dB, pt, 1, 1, 0, 0;\n"
    "mov.b32 t, %76+3586; mov.b32 u, %77+2562;\n"
    "mov.b64 dA, {t, hb}; mov.b64 dB, {u, hb};\n"
    "wgmma.mma_async.sync.aligned.m64n152k16.f32.bf16.bf16 {%0,%1,%2,%3,%4,%5,%6,%7,%8,%9,%10,%11,%12,%13,%14,%15,%16,%17,%18,%19,%20,%21,%22,%23,%24,%25,%26,%27,%28,%29,%30,%31,%32,%33,%34,%35,%36,%37,%38,%39,%40,%41,%42,%43,%44,%45,%46,%47,%48,%49,%50,%51,%52,%53,%54,%55,%56,%57,%58,%59,%60,%61,%62,%63,%64,%65,%66,%67,%68,%69,%70,%71,%72,%73,%74,%75}, dA, dB, pt, 1, 1, 0, 0;\n"
    "wgmma.commit_group.sync.aligned;\n"
    "wgmma.wait_group.sync.aligned 1;\n"
    "mov.b32 t, %79+8;\n"
    "@pe mbarrier.arrive.shared::cta.b64 _, [t];\n"
    "mov.b32 t, %76+3588; mov.b32 u, %77+2564;\n"
    "mov.b64 dA, {t, hb}; mov.b64 dB, {u, hb};\n"
    "wgmma.mma_async.sync.aligned.m64n152k16.f32.bf16.bf16 {%0,%1,%2,%3,%4,%5,%6,%7,%8,%9,%10,%11,%12,%13,%14,%15,%16,%17,%18,%19,%20,%21,%22,%23,%24,%25,%26,%27,%28,%29,%30,%31,%32,%33,%34,%35,%36,%37,%38,%39,%40,%41,%42,%43,%44,%45,%46,%47,%48,%49,%50,%51,%52,%53,%54,%55,%56,%57,%58,%59,%60,%61,%62,%63,%64,%65,%66,%67,%68,%69,%70,%71,%72,%73,%74,%75}, dA, dB, pt, 1, 1, 0, 0;\n"
    "mov.b32 t, %76+3590; mov.b32 u, %77+2566;\n"
    "mov.b64 dA, {t, hb}; mov.b64 dB, {u, hb};\n"
    "wgmma.mma_async.sync.aligned.m64n152k16.f32.bf16.bf16 {%0,%1,%2,%3,%4,%5,%6,%7,%8,%9,%10,%11,%12,%13,%14,%15,%16,%17,%18,%19,%20,%21,%22,%23,%24,%25,%26,%27,%28,%29,%30,%31,%32,%33,%34,%35,%36,%37,%38,%39,%40,%41,%42,%43,%44,%45,%46,%47,%48,%49,%50,%51,%52,%53,%54,%55,%56,%57,%58,%59,%60,%61,%62,%63,%64,%65,%66,%67,%68,%69,%70,%71,%72,%73,%74,%75}, dA, dB, pt, 1, 1, 0, 0;\n"
    "wgmma.commit_group.sync.aligned;\n"
    "mov.b32 t, %78+24;\n"
    "W8: mbarrier.try_wait.parity.shared::cta.b64 pw, [t], 1, 100000;\n"
    "@!pw bra W8;\n"
    "wgmma.fence.sync.aligned;\n"
    "mov.b32 t, %76+4096; mov.b32 u, %77+3840;\n"
    "mov.b64 dA, {t, hb}; mov.b64 dB, {u, hb};\n"
    "wgmma.mma_async.sync.aligned.m64n152k16.f32.bf16.bf16 {%0,%1,%2,%3,%4,%5,%6,%7,%8,%9,%10,%11,%12,%13,%14,%15,%16,%17,%18,%19,%20,%21,%22,%23,%24,%25,%26,%27,%28,%29,%30,%31,%32,%33,%34,%35,%36,%37,%38,%39,%40,%41,%42,%43,%44,%45,%46,%47,%48,%49,%50,%51,%52,%53,%54,%55,%56,%57,%58,%59,%60,%61,%62,%63,%64,%65,%66,%67,%68,%69,%70,%71,%72,%73,%74,%75}, dA, dB, pt, 1, 1, 0, 0;\n"
    "mov.b32 t, %76+4098; mov.b32 u, %77+3842;\n"
    "mov.b64 dA, {t, hb}; mov.b64 dB, {u, hb};\n"
    "wgmma.mma_async.sync.aligned.m64n152k16.f32.bf16.bf16 {%0,%1,%2,%3,%4,%5,%6,%7,%8,%9,%10,%11,%12,%13,%14,%15,%16,%17,%18,%19,%20,%21,%22,%23,%24,%25,%26,%27,%28,%29,%30,%31,%32,%33,%34,%35,%36,%37,%38,%39,%40,%41,%42,%43,%44,%45,%46,%47,%48,%49,%50,%51,%52,%53,%54,%55,%56,%57,%58,%59,%60,%61,%62,%63,%64,%65,%66,%67,%68,%69,%70,%71,%72,%73,%74,%75}, dA, dB, pt, 1, 1, 0, 0;\n"
    "wgmma.commit_group.sync.aligned;\n"
    "wgmma.wait_group.sync.aligned 1;\n"
    "mov.b32 t, %79+16;\n"
    "@pe mbarrier.arrive.shared::cta.b64 _, [t];\n"
    "mov.b32 t, %76+4100; mov.b32 u, %77+3844;\n"
    "mov.b64 dA, {t, hb}; mov.b64 dB, {u, hb};\n"
    "wgmma.mma_async.sync.aligned.m64n152k16.f32.bf16.bf16 {%0,%1,%2,%3,%4,%5,%6,%7,%8,%9,%10,%11,%12,%13,%14,%15,%16,%17,%18,%19,%20,%21,%22,%23,%24,%25,%26,%27,%28,%29,%30,%31,%32,%33,%34,%35,%36,%37,%38,%39,%40,%41,%42,%43,%44,%45,%46,%47,%48,%49,%50,%51,%52,%53,%54,%55,%56,%57,%58,%59,%60,%61,%62,%63,%64,%65,%66,%67,%68,%69,%70,%71,%72,%73,%74,%75}, dA, dB, pt, 1, 1, 0, 0;\n"
    "mov.b32 t, %76+4102; mov.b32 u, %77+3846;\n"
    "mov.b64 dA, {t, hb}; mov.b64 dB, {u, hb};\n"
    "wgmma.mma_async.sync.aligned.m64n152k16.f32.bf16.bf16 {%0,%1,%2,%3,%4,%5,%6,%7,%8,%9,%10,%11,%12,%13,%14,%15,%16,%17,%18,%19,%20,%21,%22,%23,%24,%25,%26,%27,%28,%29,%30,%31,%32,%33,%34,%35,%36,%37,%38,%39,%40,%41,%42,%43,%44,%45,%46,%47,%48,%49,%50,%51,%52,%53,%54,%55,%56,%57,%58,%59,%60,%61,%62,%63,%64,%65,%66,%67,%68,%69,%70,%71,%72,%73,%74,%75}, dA, dB, pt, 1, 1, 0, 0;\n"
    "wgmma.commit_group.sync.aligned;\n"
    "mov.b32 t, %78+32;\n"
    "W9: mbarrier.try_wait.parity.shared::cta.b64 pw, [t], 1, 100000;\n"
    "@!pw bra W9;\n"
    "wgmma.fence.sync.aligned;\n"
    "mov.b32 t, %76+4608; mov.b32 u, %77+5120;\n"
    "mov.b64 dA, {t, hb}; mov.b64 dB, {u, hb};\n"
    "wgmma.mma_async.sync.aligned.m64n152k16.f32.bf16.bf16 {%0,%1,%2,%3,%4,%5,%6,%7,%8,%9,%10,%11,%12,%13,%14,%15,%16,%17,%18,%19,%20,%21,%22,%23,%24,%25,%26,%27,%28,%29,%30,%31,%32,%33,%34,%35,%36,%37,%38,%39,%40,%41,%42,%43,%44,%45,%46,%47,%48,%49,%50,%51,%52,%53,%54,%55,%56,%57,%58,%59,%60,%61,%62,%63,%64,%65,%66,%67,%68,%69,%70,%71,%72,%73,%74,%75}, dA, dB, pt, 1, 1, 0, 0;\n"
    "mov.b32 t, %76+4610; mov.b32 u, %77+5122;\n"
    "mov.b64 dA, {t, hb}; mov.b64 dB, {u, hb};\n"
    "wgmma.mma_async.sync.aligned.m64n152k16.f32.bf16.bf16 {%0,%1,%2,%3,%4,%5,%6,%7,%8,%9,%10,%11,%12,%13,%14,%15,%16,%17,%18,%19,%20,%21,%22,%23,%24,%25,%26,%27,%28,%29,%30,%31,%32,%33,%34,%35,%36,%37,%38,%39,%40,%41,%42,%43,%44,%45,%46,%47,%48,%49,%50,%51,%52,%53,%54,%55,%56,%57,%58,%59,%60,%61,%62,%63,%64,%65,%66,%67,%68,%69,%70,%71,%72,%73,%74,%75}, dA, dB, pt, 1, 1, 0, 0;\n"
    "wgmma.commit_group.sync.aligned;\n"
    "wgmma.wait_group.sync.aligned 1;\n"
    "mov.b32 t, %79+24;\n"
    "@pe mbarrier.arrive.shared::cta.b64 _, [t];\n"
    "@pe mbarrier.arrive.shared::cta.b64 _, [%81];\n"
    "wgmma.fence.sync.aligned;\n"
    "mov.b32 t, %76+4612; mov.b32 u, %77+5124;\n"
    "mov.b64 dA, {t, hb}; mov.b64 dB, {u, hb};\n"
    "wgmma.mma_async.sync.aligned.m64n152k16.f32.bf16.bf16 {%0,%1,%2,%3,%4,%5,%6,%7,%8,%9,%10,%11,%12,%13,%14,%15,%16,%17,%18,%19,%20,%21,%22,%23,%24,%25,%26,%27,%28,%29,%30,%31,%32,%33,%34,%35,%36,%37,%38,%39,%40,%41,%42,%43,%44,%45,%46,%47,%48,%49,%50,%51,%52,%53,%54,%55,%56,%57,%58,%59,%60,%61,%62,%63,%64,%65,%66,%67,%68,%69,%70,%71,%72,%73,%74,%75}, dA, dB, pt, 1, 1, 0, 0;\n"
    "mov.b32 t, %76+4614; mov.b32 u, %77+5126;\n"
    "mov.b64 dA, {t, hb}; mov.b64 dB, {u, hb};\n"
    "wgmma.mma_async.sync.aligned.m64n152k16.f32.bf16.bf16 {%0,%1,%2,%3,%4,%5,%6,%7,%8,%9,%10,%11,%12,%13,%14,%15,%16,%17,%18,%19,%20,%21,%22,%23,%24,%25,%26,%27,%28,%29,%30,%31,%32,%33,%34,%35,%36,%37,%38,%39,%40,%41,%42,%43,%44,%45,%46,%47,%48,%49,%50,%51,%52,%53,%54,%55,%56,%57,%58,%59,%60,%61,%62,%63,%64,%65,%66,%67,%68,%69,%70,%71,%72,%73,%74,%75}, dA, dB, pt, 1, 1, 0, 0;\n"
    "wgmma.commit_group.sync.aligned;\n"
    "}\n"
    : "=f"(d[0]),"=f"(d[1]),"=f"(d[2]),"=f"(d[3]),"=f"(d[4]),"=f"(d[5]),"=f"(d[6]),"=f"(d[7]),"=f"(d[8]),"=f"(d[9]),"=f"(d[10]),"=f"(d[11]),"=f"(d[12]),"=f"(d[13]),"=f"(d[14]),"=f"(d[15]),"=f"(d[16]),"=f"(d[17]),"=f"(d[18]),"=f"(d[19]),"=f"(d[20]),"=f"(d[21]),"=f"(d[22]),"=f"(d[23]),"=f"(d[24]),"=f"(d[25]),"=f"(d[26]),"=f"(d[27]),"=f"(d[28]),"=f"(d[29]),"=f"(d[30]),"=f"(d[31]),"=f"(d[32]),"=f"(d[33]),"=f"(d[34]),"=f"(d[35]),"=f"(d[36]),"=f"(d[37]),"=f"(d[38]),"=f"(d[39]),"=f"(d[40]),"=f"(d[41]),"=f"(d[42]),"=f"(d[43]),"=f"(d[44]),"=f"(d[45]),"=f"(d[46]),"=f"(d[47]),"=f"(d[48]),"=f"(d[49]),"=f"(d[50]),"=f"(d[51]),"=f"(d[52]),"=f"(d[53]),"=f"(d[54]),"=f"(d[55]),"=f"(d[56]),"=f"(d[57]),"=f"(d[58]),"=f"(d[59]),"=f"(d[60]),"=f"(d[61]),"=f"(d[62]),"=f"(d[63]),"=f"(d[64]),"=f"(d[65]),"=f"(d[66]),"=f"(d[67]),"=f"(d[68]),"=f"(d[69]),"=f"(d[70]),"=f"(d[71]),"=f"(d[72]),"=f"(d[73]),"=f"(d[74]),"=f"(d[75])
    : "n"(desc_lo(A_X, 16)), "n"(desc_lo(A_RING, 16)), "n"(BAR_FULL), "n"(BAR_EMPTY), "n"(kHiSw128), "r"(tok)
    : "memory");
}
__device__ __forceinline__ void a_mainloop160(float* d, uint32_t da, uint32_t ph, int n, uint32_t xw, uint32_t tok) {
  asm volatile(
    "{ .reg .pred pe, pw, pl, ps, pt; .reg .b32 da, ha, hb, ph, n, xw, pa, fb, t, u; .reg .b64 dA, dB;\n"
    "mov.b32 da, %80; mov.b32 ph, %81; mov.b32 n, %82; mov.b32 xw, %83; mov.b32 fb, %85; mov.b32 pa, %87; mov.b32 hb, %88; mov.b32 ha, %89;\n"
    "mov.u32 t, %%laneid; setp.lt.u32 pe, t, 2; setp.eq.b32 ps, 0, 0; setp.eq.b32 pt, 0, 0;\n"
    "LOOP:\n"
    "X0: mbarrier.try_wait.parity.shared::cta.b64 pw, [xw+-24], 0, 100000;\n"
    "@!pw bra X0;\n"
    "W0: mbarrier.try_wait.parity.shared::cta.b64 pw, [fb+0], ph, 100000;\n"
    "@!pw bra W0;\n"
    "wgmma.fence.sync.aligned;\n"
    "add.u32 t, da, 0; mov.b32 u, %84+0;\n"
    "mov.b64 dA, {t, ha}; mov.b64 dB, {u, hb};\n"
    "wgmma.mma_async.sync.aligned.m64n160k16.f32.bf16.bf16 {%0,%1,%2,%3,%4,%5,%6,%7,%8,%9,%10,%11,%12,%13,%14,%15,%16,%17,%18,%19,%20,%21,%22,%23,%24,%25,%26,%27,%28,%29,%30,%31,%32,%33,%34,%35,%36,%37,%38,%39,%40,%41,%42,%43,%44,%45,%46,%47,%48,%49,%50,%51,%52,%53,%54,%55,%56,%57,%58,%59,%60,%61,%62,%63,%64,%65,%66,%67,%68,%69,%70,%71,%72,%73,%74,%75,%76,%77,%78,%79}, dA, dB, ps, 1, 1, 0, 0;\n"
    "add.u32 t, da, 128; mov.b32 u, %84+2;\n"
    "mov.b64 dA, {t, ha}; mov.b64 dB, {u, hb};\n"
    "wgmma.mma_async.sync.aligned.m64n160k16.f32.bf16.bf16 {%0,%1,%2,%3,%4,%5,%6,%7,%8,%9,%10,%11,%12,%13,%14,%15,%16,%17,%18,%19,%20,%21,%22,%23,%24,%25,%26,%27,%28,%29,%30,%31,%32,%33,%34,%35,%36,%37,%38,%39,%40,%41,%42,%43,%44,%45,%46,%47,%48,%49,%50,%51,%52,%53,%54,%55,%56,%57,%58,%59,%60,%61,%62,%63,%64,%65,%66,%67,%68,%69,%70,%71,%72,%73,%74,%75,%76,%77,%78,%79}, dA, dB, pt, 1, 1, 0, 0;\n"
    "wgmma.commit_group.sync.aligned;\n"
    "wgmma.wait_group.sync.aligned 1;\n"
    "@pe mbarrier.arrive.shared::cta.b64 _, [pa];\n"
    "add.u32 t, da, 256; mov.b32 u, %84+4;\n"
    "mov.b64 dA, {t, ha}; mov.b64 dB, {u, hb};\n"
    "wgmma.mma_async.sync.aligned.m64n160k16.f32.bf16.bf16 {%0,%1,%2,%3,%4,%5,%6,%7,%8,%9,%10,%11,%12,%13,%14,%15,%16,%17,%18,%19,%20,%21,%22,%23,%24,%25,%26,%27,%28,%29,%30,%31,%32,%33,%34,%35,%36,%37,%38,%39,%40,%41,%42,%43,%44,%45,%46,%47,%48,%49,%50,%51,%52,%53,%54,%55,%56,%57,%58,%59,%60,%61,%62,%63,%64,%65,%66,%67,%68,%69,%70,%71,%72,%73,%74,%75,%76,%77,%78,%79}, dA, dB, pt, 1, 1, 0, 0;\n"
    "add.u32 t, da, 384; mov.b32 u, %84+6;\n"
    "mov.b64 dA, {t, ha}; mov.b64 dB, {u, hb};\n"
    "wgmma.mma_async.sync.aligned.m64n160k16.f32.bf16.bf16 {%0,%1,%2,%3,%4,%5,%6,%7,%8,%9,%10,%11,%12,%13,%14,%15,%16,%17,%18,%19,%20,%21,%22,%23,%24,%25,%26,%27,%28,%29,%30,%31,%32,%33,%34,%35,%36,%37,%38,%39,%40,%41,%42,%43,%44,%45,%46,%47,%48,%49,%50,%51,%52,%53,%54,%55,%56,%57,%58,%59,%60,%61,%62,%63,%64,%65,%66,%67,%68,%69,%70,%71,%72,%73,%74,%75,%76,%77,%78,%79}, dA, dB, pt, 1, 1, 0, 0;\n"
    "wgmma.commit_group.sync.aligned;\n"
    "W1: mbarrier.try_wait.parity.shared::cta.b64 pw, [fb+8], ph, 100000;\n"
    "@!pw bra W1;\n"
    "wgmma.fence.sync.aligned;\n"
    "add.u32 t, da, 512; mov.b32 u, %84+1280;\n"
    "mov.b64 dA, {t, ha}; mov.b64 dB, {u, hb};\n"
    "wgmma.mma_async.sync.aligned.m64n160k16.f32.bf16.bf16 {%0,%1,%2,%3,%4,%5,%6,%7,%8,%9,%10,%11,%12,%13,%14,%15,%16,%17,%18,%19,%20,%21,%22,%23,%24,%25,%26,%27,%28,%29,%30,%31,%32,%33,%34,%35,%36,%37,%38,%39,%40,%41,%42,%43,%44,%45,%46,%47,%48,%49,%50,%51,%52,%53,%54,%55,%56,%57,%58,%59,%60,%61,%62,%63,%64,%65,%66,%67,%68,%69,%70,%71,%72,%73,%74,%75,%76,%77,%78,%79}, dA, dB, pt, 1, 1, 0, 0;\n"
    "add.u32 t, da, 640; mov.b32 u, %84+1282;\n"
    "mov.b64 dA, {t, ha}; mov.b64 dB, {u, hb};\n"
    "wgmma.mma_async.sync.aligned.m64n160k16.f32.bf16.bf16 {%0,%1,%2,%3,%4,%5,%6,%7,%8,%9,%10,%11,%12,%13,%14,%15,%16,%17,%18,%19,%20,%21,%22,%23,%24,%25,%26,%27,%28,%29,%30,%31,%32,%33,%34,%35,%36,%37,%38,%39,%40,%41,%42,%43,%44,%45,%46,%47,%48,%49,%50,%51,%52,%53,%54,%55,%56,%57,%58,%59,%60,%61,%62,%63,%64,%65,%66,%67,%68,%69,%70,%71,%72,%73,%74,%75,%76,%77,%78,%79}, dA, dB, pt, 1, 1, 0, 0;\n"
    "wgmma.commit_group.sync.aligned;\n"
    "wgmma.wait_group.sync.aligned 1;\n"
    "@pe mbarrier.arrive.shared::cta.b64 _, [fb+%86+0];\n"
    "add.u32 t, da, 768; mov.b32 u, %84+1284;\n"
    "mov.b64 dA, {t, ha}; mov.b64 dB, {u, hb};\n"
    "wgmma.mma_async.sync.aligned.m64n160k16.f32.bf16.bf16 {%0,%1,%2,%3,%4,%5,%6,%7,%8,%9,%10,%11,%12,%13,%14,%15,%16,%17,%18,%19,%20,%21,%22,%23,%24,%25,%26,%27,%28,%29,%30,%31,%32,%33,%34,%35,%36,%37,%38,%39,%40,%41,%42,%43,%44,%45,%46,%47,%48,%49,%50,%51,%52,%53,%54,%55,%56,%57,%58,%59,%60,%61,%62,%63,%64,%65,%66,%67,%68,%69,%70,%71,%72,%73,%74,%75,%76,%77,%78,%79}, dA, dB, pt, 1, 1, 0, 0;\n"
    "add.u32 t, da, 896; mov.b32 u, %84+1286;\n"
    "mov.b64 dA, {t, ha}; mov.b64 dB, {u, hb};\n"
    "wgmma.mma_async.sync.aligned.m64n160k16.f32.bf16.bf16 {%0,%1,%2,%3,%4,%5,%6,%7,%8,%9,%10,%11,%12,%13,%14,%15,%16,%17,%18,%19,%20,%21,%22,%23,%24,%25,%26,%27,%28,%29,%30,%31,%32,%33,%34,%35,%36,%37,%38,%39,%40,%41,%42,%43,%44,%45,%46,%47,%48,%49,%50,%51,%52,%53,%54,%55,%56,%57,%58,%59,%60,%61,%62,%63,%64,%65,%66,%67,%68,%69,%70,%71,%72,%73,%74,%75,%76,%77,%78,%79}, dA, dB, pt, 1, 1, 0, 0;\n"
    "wgmma.commit_group.sync.aligned;\n"
    "W2: mbarrier.try_wait.parity.shared::cta.b64 pw, [fb+16], ph, 100000;\n"
    "@!pw bra W2;\n"
    "wgmma.fence.sync.aligned;\n"
    "add.u32 t, da, 1024; mov.b32 u, %84+2560;\n"
    "mov.b64 dA, {t, ha}; mov.b64 dB, {u, hb};\n"
    "wgmma.mma_async.sync.aligned.m64n160k16.f32.bf16.bf16 {%0,%1,%2,%3,%4,%5,%6,%7,%8,%9,%10,%11,%12,%13,%14,%15,%16,%17,%18,%19,%20,%21,%22,%23,%24,%25,%26,%27,%28,%29,%30,%31,%32,%33,%34,%35,%36,%37,%38,%39,%40,%41,%42,%43,%44,%45,%46,%47,%48,%49,%50,%51,%52,%53,%54,%55,%56,%57,%58,%59,%60,%61,%62,%63,%64,%65,%66,%67,%68,%69,%70,%71,%72,%73,%74,%75,%76,%77,%78,%79}, dA, dB, pt, 1, 1, 0, 0;\n"
    "add.u32 t, da, 1152; mov.b32 u, %84+2562;\n"
    "mov.b64 dA, {t, ha}; mov.b64 dB, {u, hb};\n"
    "wgmma.mma_async.sync.aligned.m64n160k16.f32.bf16.bf16 {%0,%1,%2,%3,%4,%5,%6,%7,%8,%9,%10,%11,%12,%13,%14,%15,%16,%17,%18,%19,%20,%21,%22,%23,%24,%25,%26,%27,%28,%29,%30,%31,%32,%33,%34,%35,%36,%37,%38,%39,%40,%41,%42,%43,%44,%45,%46,%47,%48,%49,%50,%51,%52,%53,%54,%55,%56,%57,%58,%59,%60,%61,%62,%63,%64,%65,%66,%67,%68,%69,%70,%71,%72,%73,%74,%75,%76,%77,%78,%79}, dA, dB, pt, 1, 1, 0, 0;\n"
    "wgmma.commit_group.sync.aligned;\n"
    "wgmma.wait_group.sync.aligned 1;\n"
    "@pe mbarrier.arrive.shared::cta.b64 _, [fb+%86+8];\n"
    "X2: mbarrier.try_wait.parity.shared::cta.b64 pw, [xw], 0, 100000;\n"
    "@!pw bra X2;\n"
    "wgmma.fence.sync.aligned;\n"
    "add.u32 t, da, 1280; mov.b32 u, %84+2564;\n"
    "mov.b64 dA, {t, ha}; mov.b64 dB, {u, hb};\n"
    "wgmma.mma_async.sync.aligned.m64n160k16.f32.bf16.bf16 {%0,%1,%2,%3,%4,%5,%6,%7,%8,%9,%10,%11,%12,%13,%14,%15,%16,%17,%18,%19,%20,%21,%22,%23,%24,%25,%26,%27,%28,%29,%30,%31,%32,%33,%34,%35,%36,%37,%38,%39,%40,%41,%42,%43,%44,%45,%46,%47,%48,%49,%50,%51,%52,%53,%54,%55,%56,%57,%58,%59,%60,%61,%62,%63,%64,%65,%66,%67,%68,%69,%70,%71,%72,%73,%74,%75,%76,%77,%78,%79}, dA, dB, pt, 1, 1, 0, 0;\n"
    "add.u32 t, da, 1408; mov.b32 u, %84+2566;\n"
    "mov.b64 dA, {t, ha}; mov.b64 dB, {u, hb};\n"
    "wgmma.mma_async.sync.aligned.m64n160k16.f32.bf16.bf16 {%0,%1,%2,%3,%4,%5,%6,%7,%8,%9,%10,%11,%12,%13,%14,%15,%16,%17,%18,%19,%20,%21,%22,%23,%24,%25,%26,%27,%28,%29,%30,%31,%32,%33,%34,%35,%36,%37,%38,%39,%40,%41,%42,%43,%44,%45,%46,%47,%48,%49,%50,%51,%52,%53,%54,%55,%56,%57,%58,%59,%60,%61,%62,%63,%64,%65,%66,%67,%68,%69,%70,%71,%72,%73,%74,%75,%76,%77,%78,%79}, dA, dB, pt, 1, 1, 0, 0;\n"
    "wgmma.commit_group.sync.aligned;\n"
    "W3: mbarrier.try_wait.parity.shared::cta.b64 pw, [fb+24], ph, 100000;\n"
    "@!pw bra W3;\n"
    "wgmma.fence.sync.aligned;\n"
    "add.u32 t, da, 1536; mov.b32 u, %84+3840;\n"
    "mov.b64 dA, {t, ha}; mov.b64 dB, {u, hb};\n"
    "wgmma.mma_async.sync.aligned.m64n160k16.f32.bf16.bf16 {%0,%1,%2,%3,%4,%5,%6,%7,%8,%9,%10,%11,%12,%13,%14,%15,%16,%17,%18,%19,%20,%21,%22,%23,%24,%25,%26,%27,%28,%29,%30,%31,%32,%33,%34,%35,%36,%37,%38,%39,%40,%41,%42,%43,%44,%45,%46,%47,%48,%49,%50,%51,%52,%53,%54,%55,%56,%57,%58,%59,%60,%61,%62,%63,%64,%65,%66,%67,%68,%69,%70,%71,%72,%73,%74,%75,%76,%77,%78,%79}, dA, dB, pt, 1, 1, 0, 0;\n"
    "add.u32 t, da, 1664; mov.b32 u, %84+3842;\n"
    "mov.b64 dA, {t, ha}; mov.b64 dB, {u, hb};\n"
    "wgmma.mma_async.sync.aligned.m64n160k16.f32.bf16.bf16 {%0,%1,%2,%3,%4,%5,%6,%7,%8,%9,%10,%11,%12,%13,%14,%15,%16,%17,%18,%19,%20,%21,%22,%23,%24,%25,%26,%27,%28,%29,%30,%31,%32,%33,%34,%35,%36,%37,%38,%39,%40,%41,%42,%43,%44,%45,%46,%47,%48,%49,%50,%51,%52,%53,%54,%55,%56,%57,%58,%59,%60,%61,%62,%63,%64,%65,%66,%67,%68,%69,%70,%71,%72,%73,%74,%75,%76,%77,%78,%79}, dA, dB, pt, 1, 1, 0, 0;\n"
    "wgmma.commit_group.sync.aligned;\n"
    "wgmma.wait_group.sync.aligned 1;\n"
    "@pe mbarrier.arrive.shared::cta.b64 _, [fb+%86+16];\n"
    "add.u32 t, da, 1792; mov.b32 u, %84+3844;\n"
    "mov.b64 dA, {t, ha}; mov.b64 dB, {u, hb};\n"
    "wgmma.mma_async.sync.aligned.m64n160k16.f32.bf16.bf16 {%0,%1,%2,%3,%4,%5,%6,%7,%8,%9,%10,%11,%12,%13,%14,%15,%16,%17,%18,%19,%20,%21,%22,%23,%24,%25,%26,%27,%28,%29,%30,%31,%32,%33,%34,%35,%36,%37,%38,%39,%40,%41,%42,%43,%44,%45,%46,%47,%48,%49,%50,%51,%52,%53,%54,%55,%56,%57,%58,%59,%60,%61,%62,%63,%64,%65,%66,%67,%68,%69,%70,%71,%72,%73,%74,%75,%76,%77,%78,%79}, dA, dB, pt, 1, 1, 0, 0;\n"
    "add.u32 t, da, 1920; mov.b32 u, %84+3846;\n"
    "mov.b64 dA, {t, ha}; mov.b64 dB, {u, hb};\n"
    "wgmma.mma_async.sync.aligned.m64n160k16.f32.bf16.bf16 {%0,%1,%2,%3,%4,%5,%6,%7,%8,%9,%10,%11,%12,%13,%14,%15,%16,%17,%18,%19,%20,%21,%22,%23,%24,%25,%26,%27,%28,%29,%30,%31,%32,%33,%34,%35,%36,%37,%38,%39,%40,%41,%42,%43,%44,%45,%46,%47,%48,%49,%50,%51,%52,%53,%54,%55,%56,%57,%58,%59,%60,%61,%62,%63,%64,%65,%66,%67,%68,%69,%70,%71,%72,%73,%74,%75,%76,%77,%78,%79}, dA, dB, pt, 1, 1, 0, 0;\n"
    "wgmma.commit_group.sync.aligned;\n"
    "W4: mbarrier.try_wait.parity.shared::cta.b64 pw, [fb+32], ph, 100000;\n"
    "@!pw bra W4;\n"
    "wgmma.fence.sync.aligned;\n"
    "add.u32 t, da, 2048; mov.b32 u, %84+5120;\n"
    "mov.b64 dA, {t, ha}; mov.b64 dB, {u, hb};\n"
    "wgmma.mma_async.sync.aligned.m64n160k16.f32.bf16.bf16 {%0,%1,%2,%3,%4,%5,%6,%7,%8,%9,%10,%11,%12,%13,%14,%15,%16,%17,%18,%19,%20,%21,%22,%23,%24,%25,%26,%27,%28,%29,%30,%31,%32,%33,%34,%35,%36,%37,%38,%39,%40,%41,%42,%43,%44,%45,%46,%47,%48,%49,%50,%51,%52,%53,%54,%55,%56,%57,%58,%59,%60,%61,%62,%63,%64,%65,%66,%67,%68,%69,%70,%71,%72,%73,%74,%75,%76,%77,%78,%79}, dA, dB, pt, 1, 1, 0, 0;\n"
    "add.u32 t, da, 2176; mov.b32 u, %84+5122;\n"
    "mov.b64 dA, {t, ha}; mov.b64 dB, {u, hb};\n"
    "wgmma.mma_async.sync.aligned.m64n160k16.f32.bf16.bf16 {%0,%1,%2,%3,%4,%5,%6,%7,%8,%9,%10,%11,%12,%13,%14,%15,%16,%17,%18,%19,%20,%21,%22,%23,%24,%25,%26,%27,%28,%29,%30,%31,%32,%33,%34,%35,%36,%37,%38,%39,%40,%41,%42,%43,%44,%45,%46,%47,%48,%49,%50,%51,%52,%53,%54,%55,%56,%57,%58,%59,%60,%61,%62,%63,%64,%65,%66,%67,%68,%69,%70,%71,%72,%73,%74,%75,%76,%77,%78,%79}, dA, dB, pt, 1, 1, 0, 0;\n"
    "wgmma.commit_group.sync.aligned;\n"
    "wgmma.wait_group.sync.aligned 1;\n"
    "@pe mbarrier.arrive.shared::cta.b64 _, [fb+%86+24];\n"
    "setp.eq.b32 pw, n, 1; selp.b32 t, %90, %87, pw;\n"
    "@pe mbarrier.arrive.shared::cta.b64 _, [t];\n"
    "add.u32 t, da, 2304; mov.b32 u, %84+5124;\n"
    "mov.b64 dA, {t, ha}; mov.b64 dB, {u, hb};\n"
    "wgmma.mma_async.sync.aligned.m64n160k16.f32.bf16.bf16 {%0,%1,%2,%3,%4,%5,%6,%7,%8,%9,%10,%11,%12,%13,%14,%15,%16,%17,%18,%19,%20,%21,%22,%23,%24,%25,%26,%27,%28,%29,%30,%31,%32,%33,%34,%35,%36,%37,%38,%39,%40,%41,%42,%43,%44,%45,%46,%47,%48,%49,%50,%51,%52,%53,%54,%55,%56,%57,%58,%59,%60,%61,%62,%63,%64,%65,%66,%67,%68,%69,%70,%71,%72,%73,%74,%75,%76,%77,%78,%79}, dA, dB, pt, 1, 1, 0, 0;\n"
    "sub.u32 n, n, 1; setp.ne.b32 pl, n, 0; setp.eq.b32 ps, 0, 0; xor.b32 ph, ph, 1; add.u32 pa, fb, %86+32; mov.b32 xw, %91;\n"
    "add.u32 t, da, 2432; mov.b32 u, %84+5126;\n"
    "mov.b64 dA, {t, ha}; mov.b64 dB, {u, hb};\n"
    "wgmma.mma_async.sync.aligned.m64n160k16.f32.bf16.bf16 {%0,%1,%2,%3,%4,%5,%6,%7,%8,%9,%10,%11,%12,%13,%14,%15,%16,%17,%18,%19,%20,%21,%22,%23,%24,%25,%26,%27,%28,%29,%30,%31,%32,%33,%34,%35,%36,%37,%38,%39,%40,%41,%42,%43,%44,%45,%46,%47,%48,%49,%50,%51,%52,%53,%54,%55,%56,%57,%58,%59,%60,%61,%62,%63,%64,%65,%66,%67,%68,%69,%70,%71,%72,%73,%74,%75,%76,%77,%78,%79}, dA, dB, pt, 1, 1, 0, 0;\n"
    "wgmma.commit_group.sync.aligned;\n"
    "add.u32 da, da, 2560;\n"
    "@pl bra LOOP; }\n"
    : "+f"(d[0]),"+f"(d[1]),"+f"(d[2]),"+f"(d[3]),"+f"(d[4]),"+f"(d[5]),"+f"(d[6]),"+f"(d[7]),"+f"(d[8]),"+f"(d[9]),"+f"(d[10]),"+f"(d[11]),"+f"(d[12]),"+f"(d[13]),"+f"(d[14]),"+f"(d[15]),"+f"(d[16]),"+f"(d[17]),"+f"(d[18]),"+f"(d[19]),"+f"(d[20]),"+f"(d[21]),"+f"(d[22]),"+f"(d[23]),"+f"(d[24]),"+f"(d[25]),"+f"(d[26]),"+f"(d[27]),"+f"(d[28]),"+f"(d[29]),"+f"(d[30]),"+f"(d[31]),"+f"(d[32]),"+f"(d[33]),"+f"(d[34]),"+f"(d[35]),"+f"(d[36]),"+f"(d[37]),"+f"(d[38]),"+f"(d[39]),"+f"(d[40]),"+f"(d[41]),"+f"(d[42]),"+f"(d[43]),"+f"(d[44]),"+f"(d[45]),"+f"(d[46]),"+f"(d[47]),"+f"(d[48]),"+f"(d[49]),"+f"(d[50]),"+f"(d[51]),"+f"(d[52]),"+f"(d[53]),"+f"(d[54]),"+f"(d[55]),"+f"(d[56]),"+f"(d[57]),"+f"(d[58]),"+f"(d[59]),"+f"(d[60]),"+f"(d[61]),"+f"(d[62]),"+f"(d[63]),"+f"(d[64]),"+f"(d[65]),"+f"(d[66]),"+f"(d[67]),"+f"(d[68]),"+f"(d[69]),"+f"(d[70]),"+f"(d[71]),"+f"(d[72]),"+f"(d[73]),"+f"(d[74]),"+f"(d[75]),"+f"(d[76]),"+f"(d[77]),"+f"(d[78]),"+f"(d[79])
    : "r"(da), "r"(ph), "r"(n), "r"(xw), "n"(desc_lo(A_RING, 16)), "n"(BAR_FULL), "n"(BAR_EMPTY - BAR_FULL),
      "n"(BAR_DUMMY), "n"(kHiSw128), "n"(kHiPlain), "r"(tok), "n"(BAR_P1)
    : "memory");
}
__device__ __forceinline__ void b_mainloop(float* d, float* e, int n, uint32_t own, uint32_t tok) {
  asm volatile(
    "{ .reg .pred pe, pw, pl, ps, pt; .reg .b32 da, db, dv, om, hb, s8, ph, n, pa, t, u; .reg .b64 dA, dB;\n"
    "mov.b32 s8, 0; mov.b32 ph, 0; mov.b32 n, %160; mov.b32 om, %167; mov.b32 pa, %164; mov.b32 hb, %165; mov.b32 dv, %166;\n"
    "mov.u32 t, %%laneid; setp.eq.u32 pe, t, 0; setp.ne.b32 ps, 0, 0; setp.eq.b32 pt, 0, 0;\n"
    "LOOP: add.u32 u, s8, %162;\n"
    "W0: mbarrier.try_wait.parity.shared::cta.b64 pw, [u], ph, 100000;\n"
    "@!pw bra W0;\n"
    "mad.lo.u32 da, s8, 288, %161; add.u32 db, da, 1024; and.b32 t, om, 1; setp.ne.u32 pw, t, 0; shr.u32 om, om, 1; mad.lo.u32 t, s8, 160, dv; selp.b32 db, t, db, pw;\n"
    "wgmma.fence.sync.aligned;\n"
    "add.u32 t, da, 0; add.u32 u, db, 0;\n"
    "mov.b64 dA, {t, hb}; mov.b64 dB, {u, hb};\n"
    "wgmma.mma_async.sync.aligned.m64n160k16.f32.bf16.bf16 {%0,%1,%2,%3,%4,%5,%6,%7,%8,%9,%10,%11,%12,%13,%14,%15,%16,%17,%18,%19,%20,%21,%22,%23,%24,%25,%26,%27,%28,%29,%30,%31,%32,%33,%34,%35,%36,%37,%38,%39,%40,%41,%42,%43,%44,%45,%46,%47,%48,%49,%50,%51,%52,%53,%54,%55,%56,%57,%58,%59,%60,%61,%62,%63,%64,%65,%66,%67,%68,%69,%70,%71,%72,%73,%74,%75,%76,%77,%78,%79}, dA, dB, ps, 1, 1, 0, 0;\n"
    "add.u32 t, da, 512; add.u32 u, db, 0;\n"
    "mov.b64 dA, {t, hb}; mov.b64 dB, {u, hb};\n"
    "wgmma.mma_async.sync.aligned.m64n160k16.f32.bf16.bf16 {%80,%81,%82,%83,%84,%85,%86,%87,%88,%89,%90,%91,%92,%93,%94,%95,%96,%97,%98,%99,%100,%101,%102,%103,%104,%105,%106,%107,%108,%109,%110,%111,%112,%113,%114,%115,%116,%117,%118,%119,%120,%121,%122,%123,%124,%125,%126,%127,%128,%129,%130,%131,%132,%133,%134,%135,%136,%137,%138,%139,%140,%141,%142,%143,%144,%145,%146,%147,%148,%149,%150,%151,%152,%153,%154,%155,%156,%157,%158,%159}, dA, dB, ps, 1, 1, 0, 0;\n"
    "wgmma.commit_group.sync.aligned;\n"
    "wgmma.wait_group.sync.aligned 1;\n"
    "@pe mbarrier.arrive.shared::cta.b64 _, [pa];\n"
    "add.u32 pa, s8, %163;\n"
    "add.u32 t, da, 2; add.u32 u, db, 2;\n"
    "mov.b64 dA, {t, hb}; mov.b64 dB, {u, hb};\n"
    "wgmma.mma_async.sync.aligned.m64n160k16.f32.bf16.bf16 {%0,%1,%2,%3,%4,%5,%6,%7,%8,%9,%10,%11,%12,%13,%14,%15,%16,%17,%18,%19,%20,%21,%22,%23,%24,%25,%26,%27,%28,%29,%30,%31,%32,%33,%34,%35,%36,%37,%38,%39,%40,%41,%42,%43,%44,%45,%46,%47,%48,%49,%50,%51,%52,%53,%54,%55,%56,%57,%58,%59,%60,%61,%62,%63,%64,%65,%66,%67,%68,%69,%70,%71,%72,%73,%74,%75,%76,%77,%78,%79}, dA, dB, pt, 1, 1, 0, 0;\n"
    "add.u32 t, da, 514; add.u32 u, db, 2;\n"
    "mov.b64 dA, {t, hb}; mov.b64 dB, {u, hb};\n"
    "wgmma.mma_async.sync.aligned.m64n160k16.f32.bf16.bf16 {%80,%81,%82,%83,%84,%85,%86,%87,%88,%89,%90,%91,%92,%93,%94,%95,%96,%97,%98,%99,%100,%101,%102,%103,%104,%105,%106,%107,%108,%109,%110,%111,%112,%113,%114,%115,%116,%117,%118,%119,%120,%121,%122,%123,%124,%125,%126,%127,%128,%129,%130,%131,%132,%133,%134,%135,%136,%137,%138,%139,%140,%141,%142,%143,%144,%145,%146,%147,%148,%149,%150,%151,%152,%153,%154,%155,%156,%157,%158,%159}, dA, dB, pt, 1, 1, 0, 0;\n"
    "add.u32 s8, s8, 8; setp.eq.b32 pw, s8, 40; @pw mov.b32 s8, 0; @pw xor.b32 ph, ph, 1; sub.u32 n, n, 1; setp.eq.b32 ps, 0, 0;\n"
    "add.u32 t, da, 4; add.u32 u, db, 4;\n"
    "mov.b64 dA, {t, hb}; mov.b64 dB, {u, hb};\n"
    "wgmma.mma_async.sync.aligned.m64n160k16.f32.bf16.bf16 {%0,%1,%2,%3,%4,%5,%6,%7,%8,%9,%10,%11,%12,%13,%14,%15,%16,%17,%18,%19,%20,%21,%22,%23,%24,%25,%26,%27,%28,%29,%30,%31,%32,%33,%34,%35,%36,%37,%38,%39,%40,%41,%42,%43,%44,%45,%46,%47,%48,%49,%50,%51,%52,%53,%54,%55,%56,%57,%58,%59,%60,%61,%62,%63,%64,%65,%66,%67,%68,%69,%70,%71,%72,%73,%74,%75,%76,%77,%78,%79}, dA, dB, pt, 1, 1, 0, 0;\n"
    "add.u32 t, da, 516; add.u32 u, db, 4;\n"
    "mov.b64 dA, {t, hb}; mov.b64 dB, {u, hb};\n"
    "wgmma.mma_async.sync.aligned.m64n160k16.f32.bf16.bf16 {%80,%81,%82,%83,%84,%85,%86,%87,%88,%89,%90,%91,%92,%93,%94,%95,%96,%97,%98,%99,%100,%101,%102,%103,%104,%105,%106,%107,%108,%109,%110,%111,%112,%113,%114,%115,%116,%117,%118,%119,%120,%121,%122,%123,%124,%125,%126,%127,%128,%129,%130,%131,%132,%133,%134,%135,%136,%137,%138,%139,%140,%141,%142,%143,%144,%145,%146,%147,%148,%149,%150,%151,%152,%153,%154,%155,%156,%157,%158,%159}, dA, dB, pt, 1, 1, 0, 0;\n"
    "setp.eq.b32 pw, n, 0; selp.b32 t, %168, %164, pw;\n"
    "@pe mbarrier.arrive.shared::cta.b64 _, [t];\n"
    "add.u32 t, da, 6; add.u32 u, db, 6;\n"
    "mov.b64 dA, {t, hb}; mov.b64 dB, {u, hb};\n"
    "wgmma.mma_async.sync.aligned.m64n160k16.f32.bf16.bf16 {%0,%1,%2,%3,%4,%5,%6,%7,%8,%9,%10,%11,%12,%13,%14,%15,%16,%17,%18,%19,%20,%21,%22,%23,%24,%25,%26,%27,%28,%29,%30,%31,%32,%33,%34,%35,%36,%37,%38,%39,%40,%41,%42,%43,%44,%45,%46,%47,%48,%49,%50,%51,%52,%53,%54,%55,%56,%57,%58,%59,%60,%61,%62,%63,%64,%65,%66,%67,%68,%69,%70,%71,%72,%73,%74,%75,%76,%77,%78,%79}, dA, dB, pt, 1, 1, 0, 0;\n"
    "add.u32 t, da, 518; add.u32 u, db, 6;\n"
    "mov.b64 dA, {t, hb}; mov.b64 dB, {u, hb};\n"
    "wgmma.mma_async.sync.aligned.m64n160k16.f32.bf16.bf16 {%80,%81,%82,%83,%84,%85,%86,%87,%88,%89,%90,%91,%92,%93,%94,%95,%96,%97,%98,%99,%100,%101,%102,%103,%104,%105,%106,%107,%108,%109,%110,%111,%112,%113,%114,%115,%116,%117,%118,%119,%120,%121,%122,%123,%124,%125,%126,%127,%128,%129,%130,%131,%132,%133,%134,%135,%136,%137,%138,%139,%140,%141,%142,%143,%144,%145,%146,%147,%148,%149,%150,%151,%152,%153,%154,%155,%156,%157,%158,%159}, dA, dB, pt, 1, 1, 0, 0;\n"
    "wgmma.commit_group.sync.aligned;\n"
    "setp.ne.b32 pl, n, 0;\n"
    "@pl bra LOOP; }\n"
    : "+f"(d[0]),"+f"(d[1]),"+f"(d[2]),"+f"(d[3]),"+f"(d[4]),"+f"(d[5]),"+f"(d[6]),"+f"(d[7]),"+f"(d[8]),"+f"(d[9]),"+f"(d[10]),"+f"(d[11]),"+f"(d[12]),"+f"(d[13]),"+f"(d[14]),"+f"(d[15]),"+f"(d[16]),"+f"(d[17]),"+f"(d[18]),"+f"(d[19]),"+f"(d[20]),"+f"(d[21]),"+f"(d[22]),"+f"(d[23]),"+f"(d[24]),"+f"(d[25]),"+f"(d[26]),"+f"(d[27]),"+f"(d[28]),"+f"(d[29]),"+f"(d[30]),"+f"(d[31]),"+f"(d[32]),"+f"(d[33]),"+f"(d[34]),"+f"(d[35]),"+f"(d[36]),"+f"(d[37]),"+f"(d[38]),"+f"(d[39]),"+f"(d[40]),"+f"(d[41]),"+f"(d[42]),"+f"(d[43]),"+f"(d[44]),"+f"(d[45]),"+f"(d[46]),"+f"(d[47]),"+f"(d[48]),"+f"(d[49]),"+f"(d[50]),"+f"(d[51]),"+f"(d[52]),"+f"(d[53]),"+f"(d[54]),"+f"(d[55]),"+f"(d[56]),"+f"(d[57]),"+f"(d[58]),"+f"(d[59]),"+f"(d[60]),"+f"(d[61]),"+f"(d[62]),"+f"(d[63]),"+f"(d[64]),"+f"(d[65]),"+f"(d[66]),"+f"(d[67]),"+f"(d[68]),"+f"(d[69]),"+f"(d[70]),"+f"(d[71]),"+f"(d[72]),"+f"(d[73]),"+f"(d[74]),"+f"(d[75]),"+f"(d[76]),"+f"(d[77]),"+f"(d[78]),"+f"(d[79]),"+f"(e[0]),"+f"(e[1]),"+f"(e[2]),"+f"(e[3]),"+f"(e[4]),"+f"(e[5]),"+f"(e[6]),"+f"(e[7]),"+f"(e[8]),"+f"(e[9]),"+f"(e[10]),"+f"(e[11]),"+f"(e[12]),"+f"(e[13]),"+f"(e[14]),"+f"(e[15]),"+f"(e[16]),"+f"(e[17]),"+f"(e[18]),"+f"(e[19]),"+f"(e[20]),"+f"(e[21]),"+f"(e[22]),"+f"(e[23]),"+f"(e[24]),"+f"(e[25]),"+f"(e[26]),"+f"(e[27]),"+f"(e[28]),"+f"(e[29]),"+f"(e[30]),"+f"(e[31]),"+f"(e[32]),"+f"(e[33]),"+f"(e[34]),"+f"(e[35]),"+f"(e[36]),"+f"(e[37]),"+f"(e[38]),"+f"(e[39]),"+f"(e[40]),"+f"(e[41]),"+f"(e[42]),"+f"(e[43]),"+f"(e[44]),"+f"(e[45]),"+f"(e[46]),"+f"(e[47]),"+f"(e[48]),"+f"(e[49]),"+f"(e[50]),"+f"(e[51]),"+f"(e[52]),"+f"(e[53]),"+f"(e[54]),"+f"(e[55]),"+f"(e[56]),"+f"(e[57]),"+f"(e[58]),"+f"(e[59]),"+f"(e[60]),"+f"(e[61]),"+f"(e[62]),"+f"(e[63]),"+f"(e[64]),"+f"(e[65]),"+f"(e[66]),"+f"(e[67]),"+f"(e[68]),"+f"(e[69]),"+f"(e[70]),"+f"(e[71]),"+f"(e[72]),"+f"(e[73]),"+f"(e[74]),"+f"(e[75]),"+f"(e[76]),"+f"(e[77]),"+f"(e[78]),"+f"(e[79])
    : "r"(n), "n"(desc_lo(B_RING, 16)), "n"(BAR_FULL), "n"(BAR_EMPTY), "n"(BAR_DUMMY), "n"(kHiSw128), "n"(desc_lo(B_STG, 16)),
      "r"(own), "r"(tok)
    : "memory");
}

__device__ __forceinline__ void mbar_init(uint32_t bar, uint32_t cnt) { asm volatile("mbarrier.init.shared::cta.b64 [%0], %1;" ::"r"(bar), "r"(cnt) : "memory"); }
__device__ __forceinline__ void mbar_init_fence() { asm volatile("fence.mbarrier_init.release.cluster;" ::: "memory"); }
__device__ __forceinline__ void mbar_arrive(uint32_t bar) { asm volatile("mbarrier.arrive.shared::cta.b64 _, [%0];" ::"r"(bar) : "memory"); }
__device__ __forceinline__ void mbar_wait(uint32_t bar, uint32_t parity) {
  asm volatile("{ .reg .pred p;\nLAB_WAIT: mbarrier.try_wait.parity.shared::cta.b64 p, [%0], %1, 100000;\n@!p bra LAB_WAIT; }" ::"r"(bar), "r"(parity) : "memory");
}
__device__ __forceinline__ void mbar_poll(uint32_t bar) {
  asm volatile("{ .reg .pred p;\nLAB_WAIT: mbarrier.test_wait.parity.shared::cta.b64 p, [%0], 0;\n@!p bra LAB_WAIT; }" ::"r"(bar) : "memory");
}
__device__ __forceinline__ void wg_bar(int wg) { asm volatile("bar.sync %0, 128;" ::"r"(wg + 1) : "memory"); }
__device__ __forceinline__ void fence_async_smem() { asm volatile("fence.proxy.async.shared::cta;" ::: "memory"); }

#define ELECT "{ .reg .pred e; elect.sync _|e, 0xffffffff;\n@e "
__device__ __forceinline__ void mbar_expect(uint32_t bar, uint32_t bytes) { asm volatile(ELECT "mbarrier.arrive.expect_tx.shared::cta.b64 _, [%0], %1; }" ::"r"(bar), "r"(bytes) : "memory"); }
__device__ __forceinline__ void mbar_arrive1(uint32_t bar) { asm volatile(ELECT "mbarrier.arrive.shared::cta.b64 _, [%0]; }" ::"r"(bar) : "memory"); }
__device__ __forceinline__ void tma2d(uint32_t dst, const CUtensorMap* m, int c0, int c1, uint32_t bar) {
  asm volatile(ELECT "cp.async.bulk.tensor.2d.shared::cluster.global.mbarrier::complete_tx::bytes [%0], [%1, {%3,%4}], [%2]; }"
               ::"r"(dst), "l"(m), "r"(bar), "r"(c0), "r"(c1) : "memory");
}
__device__ __forceinline__ void tma3d(uint32_t dst, const CUtensorMap* m, int c0, int c1, int c2, uint32_t bar) {
  asm volatile(ELECT "cp.async.bulk.tensor.3d.shared::cluster.global.mbarrier::complete_tx::bytes [%0], [%1, {%3,%4,%5}], [%2]; }"
               ::"r"(dst), "l"(m), "r"(bar), "r"(c0), "r"(c1), "r"(c2) : "memory");
}
__device__ __forceinline__ void tma5d(uint32_t dst, const CUtensorMap* m, int c0, int c3, int c4, uint32_t bar) {
  asm volatile(ELECT "cp.async.bulk.tensor.5d.shared::cluster.global.mbarrier::complete_tx::bytes [%0], [%1, {%3,%4,%4,%5,%6}], [%2]; }"
               ::"r"(dst), "l"(m), "r"(bar), "r"(c0), "r"(0), "r"(c3), "r"(c4) : "memory");
}
__device__ __forceinline__ void prefetch3d(const CUtensorMap* m, int c0, int c1, int c2) {
  asm volatile(ELECT "cp.async.bulk.prefetch.tensor.3d.L2.global [%0, {%1,%2,%3}]; }" ::"l"(m), "r"(c0), "r"(c1), "r"(c2) : "memory");
}
__device__ __forceinline__ void prefetch_l2(const void* p, uint32_t bytes) {
  asm volatile(ELECT "cp.async.bulk.prefetch.L2.global [%0], %1; }" ::"l"(p), "r"(bytes) : "memory");
}
__device__ __forceinline__ void bulk_load(uint32_t dst, const void* src, uint32_t bytes, uint32_t bar) {
  asm volatile(ELECT "cp.async.bulk.shared::cluster.global.mbarrier::complete_tx::bytes [%0], [%1], %2, [%3]; }" ::"r"(dst), "l"(src), "r"(bytes), "r"(bar) : "memory");
}
__device__ __forceinline__ void bulk_store(void* dst, uint32_t src, uint32_t bytes) {
  asm volatile(ELECT "cp.async.bulk.global.shared::cta.bulk_group [%0], [%1], %2; }" ::"l"(dst), "r"(src), "r"(bytes) : "memory");
}
__device__ __forceinline__ void bulk_reduce(void* dst, uint32_t src, uint32_t bytes) {
  asm volatile(ELECT "cp.reduce.async.bulk.global.shared::cta.bulk_group.add.noftz.bf16 [%0], [%1], %2; }" ::"l"(dst), "r"(src), "r"(bytes) : "memory");
}
__device__ __forceinline__ void bulk_wait() { asm volatile("cp.async.bulk.commit_group;\ncp.async.bulk.wait_group 0;" ::: "memory"); }
__device__ __forceinline__ void cnt_add(const Params& P, int idx) {
  asm volatile(ELECT "red.release.gpu.global.add.u32 [%0], 1; }" ::"l"(P.s->cnt + idx) : "memory");
}
__device__ __forceinline__ void cnt_wait(const Params& P, int idx, unsigned target) {
  asm volatile("{ .reg .pred p; .reg .s32 v;\nLAB_POLL: ld.acquire.gpu.global.s32 v, [%0];\nsub.s32 v, v, %1; setp.lt.s32 p, v, 0;\n"
               "@p bra LAB_POLL;\nfence.proxy.async.global; }" ::"l"(P.s->cnt + idx), "r"(target) : "memory");
}
__device__ __forceinline__ uint32_t line_wait(const Params& P, int idx, unsigned target, uint32_t need, uint32_t ns) {
  uint32_t have;
  do {
    if (ns) __nanosleep(ns);
    int v;
    asm volatile("ld.acquire.gpu.global.s32 %0, [%1];" : "=r"(v) : "l"(P.s->cnt + idx + (threadIdx.x & 31)) : "memory");
    have = __ballot_sync(~0u, v - (int)target >= 0);
  } while ((have & need) != need);
  asm volatile("fence.proxy.async.global;" ::: "memory");
  return have;
}
__device__ __forceinline__ unsigned load_epoch(const Params& P) {
  unsigned v;
  asm volatile("ld.global.cg.u32 %0, [%1];" : "=r"(v) : "l"(P.s->ep + blockIdx.x * 32) : "memory");
  return v;
}
__device__ __forceinline__ void pace(uint32_t t0, uint32_t dt) { while ((uint32_t)clock() - t0 < dt) {} }

__device__ __forceinline__ uint32_t pack2(float lo, float hi) {
  uint32_t r;
  asm("cvt.rn.bf16x2.f32 %0, %1, %2;" : "=r"(r) : "f"(hi), "f"(lo));
  return r;
}
__device__ __forceinline__ float ex2(float x) { float r; asm("ex2.approx.ftz.f32 %0, %1;" : "=f"(r) : "f"(x)); return r; }
__device__ __forceinline__ float rcp(float x) { float r; asm("rcp.approx.ftz.f32 %0, %1;" : "=f"(r) : "f"(x)); return r; }
__device__ __forceinline__ void sts128(uint32_t a, uint32_t x, uint32_t y, uint32_t z, uint32_t w) {
  asm volatile("st.shared.v4.b32 [%0], {%1,%2,%3,%4};" ::"r"(a), "r"(x), "r"(y), "r"(z), "r"(w) : "memory");
}
__device__ __forceinline__ void lds128(uint32_t a, uint32_t* r) {
  asm volatile("ld.shared.v4.b32 {%0,%1,%2,%3}, [%4];" : "=r"(r[0]), "=r"(r[1]), "=r"(r[2]), "=r"(r[3]) : "r"(a) : "memory");
}
__device__ __forceinline__ void ldsm4(uint32_t a, uint32_t* r) {
  asm volatile("ldmatrix.sync.aligned.m8n8.x4.shared.b16 {%0,%1,%2,%3}, [%4];" : "=r"(r[0]), "=r"(r[1]), "=r"(r[2]), "=r"(r[3]) : "r"(a) : "memory");
}
__device__ __forceinline__ void ldsm4t(uint32_t a, uint32_t* r) {
  asm volatile("ldmatrix.sync.aligned.m8n8.x4.trans.shared.b16 {%0,%1,%2,%3}, [%4];" : "=r"(r[0]), "=r"(r[1]), "=r"(r[2]), "=r"(r[3]) : "r"(a) : "memory");
}
__device__ __forceinline__ void stsm4(uint32_t a, uint32_t x, uint32_t y, uint32_t z, uint32_t w) {
  asm volatile("stmatrix.sync.aligned.m8n8.x4.shared.b16 [%0], {%1,%2,%3,%4};" ::"r"(a), "r"(x), "r"(y), "r"(z), "r"(w) : "memory");
}
__device__ __forceinline__ void stsm2(uint32_t a, uint32_t x, uint32_t y) {
  asm volatile("stmatrix.sync.aligned.m8n8.x2.shared.b16 [%0], {%1,%2};" ::"r"(a), "r"(x), "r"(y) : "memory");
}
__device__ __forceinline__ void stsm4t(uint32_t a, uint32_t x, uint32_t y, uint32_t z, uint32_t w) {
  asm volatile("stmatrix.sync.aligned.m8n8.x4.trans.shared.b16 [%0], {%1,%2,%3,%4};" ::"r"(a), "r"(x), "r"(y), "r"(z), "r"(w) : "memory");
}
__device__ __forceinline__ void mma16(float* d, uint32_t a0, uint32_t a1, uint32_t a2, uint32_t a3, uint32_t b0, uint32_t b1) {
  asm("mma.sync.aligned.m16n8k16.row.col.f32.bf16.bf16.f32 {%0,%1,%2,%3},{%4,%5,%6,%7},{%8,%9},{%0,%1,%2,%3};"
      : "+f"(d[0]), "+f"(d[1]), "+f"(d[2]), "+f"(d[3]) : "r"(a0), "r"(a1), "r"(a2), "r"(a3), "r"(b0), "r"(b1));
}
__device__ __forceinline__ void mma8(float* d, uint32_t a0, uint32_t a1, uint32_t b0) {
  asm("mma.sync.aligned.m16n8k8.row.col.f32.bf16.bf16.f32 {%0,%1,%2,%3},{%4,%5},{%6},{%0,%1,%2,%3};"
      : "+f"(d[0]), "+f"(d[1]), "+f"(d[2]), "+f"(d[3]) : "r"(a0), "r"(a1), "r"(b0));
}
__device__ __forceinline__ float bf_lo(uint32_t v) { return __uint_as_float(v << 16); }
__device__ __forceinline__ float bf_hi(uint32_t v) { return __uint_as_float(v & 0xffff0000u); }
__device__ __forceinline__ float ldbf(const __nv_bfloat16* p) { return __bfloat162float(__ldg(p)); }

__device__ __forceinline__ int tile_pos(int job) {
  const int grp = job / 10, kb = job - 10 * grp, w0 = grp & 1;
  return (grp & 2) * 30 + kb + (grp < 8 ? (grp >> 2) * 20 + (w0 ? 0 : 10) : w0 ? 45 : kb < 5 ? 40 : 50);
}

__device__ __forceinline__ int tile_counter(int job) {
  const int grp = job / 10;
  return C_W + (grp & 2) * 16 + (grp >> 2) * 2 + (~grp & 1);
}

__device__ __forceinline__ void a_producer(const Params& P, int rb, int half) {
  const uint32_t t0 = clock();
#pragma unroll 1
  for (int n = 3; n < 5; n++) {
    pace(t0, (n - 3) * 300);
    mbar_expect(BAR_X + 8 * (n - 1), 8192);
    tma2d(A_X + (n - 1) * 8192, &P.xa, (n - 1) * 64, rb * 64, BAR_X + 8 * (n - 1));
    mbar_expect(BAR_FULL + 8 * n, kBlob);
    tma3d(A_RING + n * kBlob, &P.wv, 0, n * 32, 20 + 5 * half, BAR_FULL + 8 * n);
    if (n == 3 && rb >= 5 && rb < 20) prefetch3d(&P.wv, 0, rb * 32, 20 + 5 * half);
  }
#pragma unroll 1
  for (int r = 1; r < 4; r++) {
#pragma unroll
    for (int s = 0; s < 5; s++) {
      mbar_wait(BAR_EMPTY + 8 * s, (r & 1) ^ 1);
      mbar_expect(BAR_FULL + 8 * s, kBlob);
      tma3d(A_RING + s * kBlob, &P.wv, 0, (5 * r + s) * 32, 20 + 5 * half, BAR_FULL + 8 * s);
      if (!(s & 1) && r < 3) {
        const int kb = 3 * r + 1 + (s >> 1);
        mbar_expect(BAR_X + 8 * kb, 8192);
        tma2d(A_X + kb * 8192, &P.xa, kb * 64, rb * 64, BAR_X + 8 * kb);
      }
    }
  }
  const unsigned char* src = P.s->w + (size_t)half * 60 * kBlob;
#pragma unroll 1
  for (int r = 0; r < 12; r++, src += 5 * kBlob) {
    mbar_wait(BAR_W + 8 * min(r >> 1, 4), 0);
    const uint32_t bytes = r < 8 ? kFold : kBlob;
#pragma unroll
    for (int s = 0; s < 5; s++) {
      mbar_wait(BAR_EMPTY + 8 * s, (r & 1) ^ 1);
      mbar_expect(BAR_FULL + 8 * s, bytes);
      bulk_load(A_RING + s * kBlob, src + s * kBlob, bytes, BAR_FULL + 8 * s);
      if (s == 3) mbar_arrive1(r == 7 ? BAR_KV0 : BAR_DUMMY);
    }
  }
}

__device__ __forceinline__ void a_poller(const Params& P, int half, unsigned ep) {
  uint32_t have = 0;
#pragma unroll 1
  for (int i = 0; i < 5; i++) {
    const uint32_t need = i < 4 ? 1 << i : 48;
    if ((have & need) != need) have = line_wait(P, C_W + half * 32, ep * 10, need, i < 2 ? 0 : 400);
    mbar_arrive1(BAR_W + 8 * i);
  }
  mbar_expect(BAR_KVR, 2 * kKv);
  mbar_wait(BAR_RED + 8, 0);
  cnt_wait(P, C_KV + (2 * half + 1) * 32, ep * 32);
  mbar_wait(BAR_KV0, 0);
  bulk_load(A_KV0, P.s->kv + (2 * half + 1) * 2 * kKv, 2 * kKv, BAR_KVR);
}

__device__ __forceinline__ void a_reducer(const Params& P, int rb, int half, unsigned ep) {
#pragma unroll 1
  for (int ty = 0; ty < 2; ty++) {
    const int hg = 2 * half + (ty ^ 1);
    unsigned char* dst = P.s->kv + (hg * 2 + (rb & 1)) * kKv;
    mbar_wait(BAR_RED + 8 * ty, 0);
#pragma unroll
    for (int i = 0; i < 8; i++) {
      const int j = (i + (rb >> 1)) & 7;
      if (i) __nanosleep(30);
      bulk_reduce(dst + j * 2048, A_PHI + kHalf + j * 2048 + (j >> 1) * (kPair - 4096), 2048);
    }
    bulk_wait();
    mbar_arrive1(ty ? BAR_STG1 : BAR_STG);
    cnt_add(P, C_KV + hg * 32);
  }
  mbar_expect(BAR_KVR + 8, 2 * kKv);
  cnt_wait(P, C_KV + 2 * half * 32, ep * 32);
  mbar_wait(BAR_QD, 0);
  bulk_load(A_KV1, P.s->kv + 2 * half * 2 * kKv, 2 * kKv, BAR_KVR + 8);
}

__device__ __forceinline__ void a_swap(const Params& P, int rb, int half, int ty, unsigned ep) {
  const int me = rb * 4 + 2 * half + ty;
  const uint32_t reg = A_X + ty * kBlob;
  mbar_expect(BAR_P + 24 * ty, kBlob);
  mbar_wait(BAR_O + 8 * ty, 0);
  bulk_store(P.s->ox + (size_t)me * kBlob, reg, kBlob);
  bulk_wait();
  cnt_add(P, C_O + me * 32);
  cnt_wait(P, C_O + (me ^ 2) * 32, ep);
  mbar_wait(BAR_O + 8, 0);
  bulk_load(reg + 2 * kBlob, P.s->ox + (size_t)(me ^ 2) * kBlob, kBlob, BAR_P + 24 * ty);
}

template <int WG>
__device__ __forceinline__ void a_vgemm(float* v) {
#pragma unroll 1
  for (int n = 0; n < 20; n++) {
    const int s = n % 5;
    mbar_wait(BAR_X + 8 * (n >> 1), 0);
    mbar_wait(BAR_FULL + 8 * s, (n / 5) & 1);
    const uint32_t da = desc_lo(A_X, 16) + (n >> 1) * 512 + (n & 1) * 4;
    const uint32_t db = desc_lo(A_RING, 4096) + s * (kBlob >> 4) + (WG ? 0 : 768);
    wg_fence();
    if (WG == 0) {
      wgmma_n128<1>(v, mkdesc(da, kHiSw128), mkdesc(db, kHiSw128), n);
      wgmma_n128<1>(v, mkdesc(da + 2, kHiSw128), mkdesc(db + 128, kHiSw128), 1);
    } else {
      wgmma_n192<1>(v, mkdesc(da, kHiSw128), mkdesc(db, kHiSw128), n);
      wgmma_n192<1>(v, mkdesc(da + 2, kHiSw128), mkdesc(db + 128, kHiSw128), 1);
    }
    wg_commit();
    wg_wait<1>();
    if (n) mbar_arrive1(BAR_EMPTY + 8 * (s ? s - 1 : 4));
  }
  wg_wait<0>();
}

constexpr float kL = 1.4426950408889634f;
__device__ __forceinline__ void softmax_stats(const float* p, float& mx, float& mn) {
  int x[2];
  unsigned n[2];
#pragma unroll
  for (int i = 0; i < 2; i++) {
    const float* a = p + 36 * i;
    x[i] = __vimax3_s32(__float_as_int(a[0]), __float_as_int(a[4]), __float_as_int(a[8]));
    n[i] = __vimax3_u32(__float_as_uint(a[0]), __float_as_uint(a[4]), __float_as_uint(a[8]));
#pragma unroll
    for (int j = 3; j < 9; j += 2) {
      x[i] = __vimax3_s32(x[i], __float_as_int(a[4 * j]), __float_as_int(a[4 * j + 4]));
      n[i] = __vimax3_u32(n[i], __float_as_uint(a[4 * j]), __float_as_uint(a[4 * j + 4]));
    }
  }
  mx = -kL * __int_as_float(__vimax3_s32_relu(x[0], x[1], __float_as_int(p[72])));
  mn = kL * fminf(__uint_as_float(__vimax3_u32(n[0], n[1], __float_as_uint(p[72]))), 0.f);
}

__device__ __forceinline__ void a_consumer(const Params& P, int rb, int half, int wg) {
  const int tid = threadIdx.x & 127, w = tid >> 5, lane = tid & 31, gi = lane >> 2, q = lane & 3;
  const int hg = 2 * half + (wg ^ 1);
  uint32_t hold[48];
  if (tid == 0) sts128(A_ONES, 0x3F803F80u, 0x3F803F80u, 0x3F803F80u, 0x3F803F80u);
  {
    float v[96];
    reg_fence<96>(v);
    if (wg == 0) a_vgemm<0>(v);
    else a_vgemm<1>(v);
    reg_fence<96>(v);
    mbar_arrive1(BAR_EMPTY + 32);
    const uint32_t vst = A_PHI + (wg ? 0 : 24576) + (lane >> 4) * 1024 + (16 * w + (lane & 15)) * 16;
#pragma unroll
    for (int cc = 0; cc < 12; cc++) {
      const int c = (cc + 10) % 12;
      if (c < 8 || wg)
        stsm4(vst + c * 2048, pack2(v[8 * c], v[8 * c + 1]), pack2(v[8 * c + 2], v[8 * c + 3]), pack2(v[8 * c + 4], v[8 * c + 5]), pack2(v[8 * c + 6], v[8 * c + 7]));
      if (cc == 1 && wg) {
        asm volatile("bar.arrive 3, 256;" ::: "memory");
        asm volatile("bar.sync 4, 256;" ::: "memory");
      }
    }
    if (wg) wg_bar(1);
    else asm volatile("bar.sync 3, 256;" ::: "memory");
    const uint32_t vb = A_PHI + (wg ? 0 : 20480) + w * 5120;
    const uint32_t va = vb + ((lane >> 3) & 1) * 1024 + ((lane & 7) + 8 * (lane >> 4)) * 16;
#pragma unroll
    for (int ks = 0; ks < 4; ks++) {
      ldsm4t(va + ks * 256, hold + 4 * ks);
      ldsm4t(va + 3072 + ks * 256, hold + 16 + 4 * ks);
      ldsm4t((lane & 8) ? A_ONES : va + 2048 + ks * 256, hold + 32 + 4 * ks);
    }
    if (wg == 0) asm volatile("bar.arrive 4, 256;" ::: "memory");
    mbar_arrive1(BAR_V);
  }
  const uint32_t pf = A_PHI + ((lane >> 3) & 1) * kHalf + w * kPair + (lane >> 4) * 512 + (lane & 7) * 16;
#pragma unroll 1
  for (int tk = 0; tk < 2; tk++) {
    const int task = uniform(tk);
    if (task == 0) {
      mbar_wait(BAR_TOK + 8 * wg, 0);
    } else {
      uint32_t b[4][20];
#pragma unroll
      for (int cp = 0; cp < 5; cp++) ldsm4t(pf + cp * 1024, b[0] + 4 * cp);
      mbar_wait(BAR_TOK + 8 * wg, 1);
      float acc[80];
#pragma unroll
      for (int i = 0; i < 80; i++) acc[i] = 0.f;
#pragma unroll
      for (int ks = 0; ks < 4; ks++)
#pragma unroll
        for (int cp = 0; cp < 5; cp++) {
          if (ks < 3) ldsm4t(pf + cp * 1024 + (ks + 1) * 128, b[ks + 1] + 4 * cp);
          if (ks == 2 && cp == 4) mbar_arrive1(BAR_FREE + 8 * wg);
#pragma unroll
          for (int c = 2 * cp; c < 2 * cp + 2; c++) {
            const uint32_t* a = hold + (c < 5 ? 0 : 16) + 4 * ks;
            const uint32_t* m = hold + 32 + 4 * ks;
            mma16(acc + 8 * c, a[0], a[1], a[2], a[3], b[ks][2 * c], b[ks][2 * c + 1]);
            mma16(acc + 8 * c + 4, m[0], m[1], m[2], m[3], b[ks][2 * c], b[ks][2 * c + 1]);
          }
        }
      uint32_t f[32];
#pragma unroll
      for (int c = 0; c < 10; c++) {
        const float* x = acc + 8 * c;
        const int h2 = c / 5, i = (c + 4 * h2) % 5, st = i < 4 ? 4 : 1, o = 16 * h2 + (i < 4 ? i : 12);
        const bool isv = (gi >> 2) == h2;
        f[o] = pack2(x[0], x[1]);
        f[o + st] = pack2(x[2], x[3]);
        f[o + 2 * st] = pack2(isv ? x[4] : x[6], isv ? x[5] : x[7]);
      }
      f[15] = f[31] = 0;
#pragma unroll
      for (int i = 0; i < 8; i++) sts128(A_PHI + kHalf + w * kPair + i * 512 + lane * 16, f[4 * i], f[4 * i + 1], f[4 * i + 2], f[4 * i + 3]);
      fence_async_smem();
      mbar_arrive1(BAR_RED + 8 * wg);
    }
    float acc[76];
    a_mainloop152(acc, BAR_TOK + 8 * (wg ^ 1));
    wg_wait<0>();
    reg_fence<76>(acc);
    if (lane < 2) mbar_arrive(BAR_EMPTY + 32);
    if (task & wg) mbar_arrive1(BAR_QD);

    const uint32_t gate0 = task ? (wg ? BAR_QF : BAR_FREE + 8) : (wg ? BAR_FREE : BAR_V);
    const uint32_t gate1 = task ? (wg ? BAR_QF + 8 : BAR_STG1) : (wg ? BAR_STG : BAR_V);
    mbar_wait(gate0, 0);
    mbar_poll(gate0);
    reg_fence<76>(acc);
    const uint32_t pa = A_PHI + q * kPair + (8 * w + gi) * 16;
    float mx[4], mn[4], t[20], sum = 0.f;
    uint32_t e[2][10], k[40], r2 = 0;
#pragma unroll
    for (int g = 0; g < 4; g++) softmax_stats(acc + g, mx[g], mn[g]);
#pragma unroll
    for (int i = 0; i <= 8; i++) {
      const int g = i >> 1, pv = i - 1;
      if (i == 5) mbar_wait(gate1, 0);
      const float* p = acc + g;
      const float sg = (i & 1) ? -kL : kL, m = i < 8 ? ((i & 1) ? mn[g] : mx[g]) : 0.f;
#pragma unroll
      for (int j = 0; j < 23; j++) {
        if (i < 8 && j < 20) t[j] = ex2(j ? fmaf(p[4 * (j - 1)], sg, m) : m);
        if (i < 8 && j >= 3) {
          const int x = j - 3;
          sum = x ? sum + t[x] : t[0];
          if (x & 1) e[i & 1][x >> 1] = pack2(t[x - 1], t[x]);
        }
        if (i && j >= 2 && j < 12) {
          const int x = j - 2, o = 10 * (pv & 3) + x;
          asm("mul.rn.bf16x2 %0, %1, %2;" : "=r"(k[o]) : "r"(e[pv & 1][x]), "r"(r2));
          if ((o & 3) == 3) sts128(pa + (pv >> 2) * kHalf + (o >> 2) * 512, k[o - 3], k[o - 2], k[o - 1], k[o]);
        }
      }
      if (i && (pv & 3) == 3) mbar_arrive1(task ? BAR_QS + 16 * wg + 2 * (pv & 4) : BAR_DUMMY);
      if (i < 8) {
        const float r = rcp(sum);
        r2 = pack2(r, r);
      }
    }
    if (task == 0) wg_bar(wg);
  }
#pragma unroll 1
  for (int jb = 3 * wg; jb < 3 + wg; jb++) {
    const int job = uniform(jb), ty = job >> 1, hi = job & 1;
    mbar_wait(BAR_QS + 8 * job, 0);
    uint32_t aa[2][20];
    const uint32_t pn = A_PHI + hi * kHalf + w * kPair + (lane >> 4) * 512 + (lane & 15) * 16;
#pragma unroll
    for (int i = 0; i < 10; i++) ldsm4(pn + ((i + 2) % 5) * 1024 + (i / 5) * 256, aa[i / 5] + 4 * ((i + 2) % 5));
    mbar_arrive1(ty ? BAR_DUMMY : BAR_QF + 8 * hi);
    if (job != 1) {
      mbar_wait(BAR_KVR + 8 * ty, 0);
#pragma unroll
      for (int i = 0; i < 8; i++) {
        const uint32_t ka = (ty ? A_KV1 : A_KV0) + w * 4096 + i * 512 + lane * 16;
        uint32_t x[4];
        lds128(ka, hold + 4 * i);
        lds128(ka + kKv, x);
#pragma unroll
        for (int k = 0; k < 4; k++) asm("add.rn.bf16x2 %0, %0, %1;" : "+r"(hold[4 * i + k]) : "r"(x[k]));
      }
      if (job == 0) {
        wg_bar(0);
        mbar_wait(BAR_TOK, 0);
      }
    }
    const uint32_t oa = A_X + ty * kBlob + (5 * w + (lane >> 4)) * 1024 + ((lane & 7) + 2 * (lane & 8) + 8 * hi) * 16;
#pragma unroll
    for (int u = 0; u < 2; u++) {
      const uint32_t* a = aa[u];
      float d[2][12];
#pragma unroll
      for (int h2 = 0; h2 < 2; h2++) {
        const uint32_t* b = hold + 16 * h2;
#pragma unroll
        for (int i = 0; i < 12; i++) d[h2][i] = 0.f;
        const uint32_t* a8 = a + 8 + 2 * h2;
        const uint32_t* a16 = a + 12 * h2;
#pragma unroll
        for (int j = 2; j >= 0; j--) {
          mma8(d[h2] + 4 * j, a8[0], a8[1], b[12 + j]);
          mma16(d[h2] + 4 * j, a16[0], a16[1], a16[2], a16[3], b[4 * j], b[4 * j + 1]);
          mma16(d[h2] + 4 * j, a16[4], a16[5], a16[6], a16[7], b[4 * j + 2], b[4 * j + 3]);
        }
      }
      uint32_t o[10];
#pragma unroll
      for (int hh = 0; hh < 2; hh++) {
        const bool up = q & 2;
        const float r0 = rcp((up ? d[0][8 + 2 * hh] : d[1][8 + 2 * hh]) + 1e-6f);
        const float r1 = __shfl_xor_sync(~0u, r0, 2);
        const float ra = up ? r0 : r1, rb2 = up ? r1 : r0;
        o[0 + hh] = pack2(d[0][2 * hh] * ra, d[0][2 * hh + 1] * ra);
        o[2 + hh] = pack2(d[0][4 + 2 * hh] * ra, d[0][5 + 2 * hh] * ra);
        o[4 + hh] = pack2((up ? d[1][8 + 2 * hh] : d[0][8 + 2 * hh]) * r1, (up ? d[1][9 + 2 * hh] : d[0][9 + 2 * hh]) * r1);
        o[6 + hh] = pack2(d[1][2 * hh] * rb2, d[1][2 * hh + 1] * rb2);
        o[8 + hh] = pack2(d[1][4 + 2 * hh] * rb2, d[1][5 + 2 * hh] * rb2);
      }
      stsm4(oa + u * 512, o[0], o[1], o[2], o[3]);
      stsm4(oa + u * 512 + 2048, o[4], o[5], o[6], o[7]);
      stsm2(oa + u * 512 + 4096, o[8], o[9]);
    }
    fence_async_smem();
    mbar_arrive1(BAR_O + 8 * ty);
  }
  float acc[80];
#pragma unroll
  for (int i = 0; i < 80; i++) acc[i] = 0.f;
  reg_fence<80>(acc);
#pragma unroll 1
  for (int rr = wg ^ 1; rr <= P.one; rr++) {
    const int r = uniform(rr);
    mbar_wait(r ? BAR_TOK + 8 * wg : BAR_O + 8, r & ~wg);
    a_mainloop160(acc, desc_lo(A_X, 1024) + (r & wg) * 2560, r, 2 - wg, (r & wg) ? BAR_P1 : BAR_O + 8, BAR_TOK + 8 * (wg ^ 1));
    wg_wait<0>();
    reg_fence<80>(acc);
    if (lane < 2) mbar_arrive(BAR_EMPTY + 32);
  }
  mbar_arrive1(BAR_DONE);
  float* o = P.out + (size_t)(rb * 64 + 16 * w + gi) * 1280 + 160 * hg + 4 * q;
#pragma unroll
  for (int jp = 0; jp < 10; jp++)
#pragma unroll
    for (int hh = 0; hh < 2; hh++)
      *reinterpret_cast<float4*>(o + hh * 8 * 1280 + 16 * jp) =
          make_float4(acc[8 * jp + 2 * hh], acc[8 * jp + 2 * hh + 1], acc[8 * jp + 4 + 2 * hh], acc[8 * jp + 5 + 2 * hh]);
}

__device__ __forceinline__ void fold_load(const Params& P, int job, uint32_t buf, uint32_t bar, uint32_t bar_phi) {
  const int grp = job / 10, kb = job - 10 * grp;
  const int col = (grp & 3) * 160 + (grp < 4 ? 640 : 0);
  mbar_expect(bar_phi, kPrepPhi);
  bulk_load(buf + kPrepW, P.wphi + (grp & 3) * 3200, kPrepPhi, bar_phi);
  mbar_expect(bar, kPrepW);
#pragma unroll
  for (int i = 0; i < 3; i++) tma5d(buf + i * 8192, &P.wp, col + i * 64, 0, 2 * kb, bar);
}
__device__ __forceinline__ void wo_load(const Params& P, int job, uint32_t buf, uint32_t bar) {
  const int ns = job / 10, kb = job - 10 * ns;
  mbar_expect(bar, kPrepW);
#pragma unroll 1
  for (int i = 0; i < 6; i++) {
    const int u = 2 * kb + (i & 1), pos = u / 5;
    tma5d(buf + i * 4096, &P.wop, ns * 160 + (i >> 1) * 64, 0, 5 * (2 * (((ns ^ pos) >> 1) & 1) + 1 - (pos & 1) - pos) + u, bar);
  }
}

__device__ __forceinline__ void prep_fold(uint32_t buf, uint32_t bar, uint32_t bar_phi) {
  const int tid = threadIdx.x, hl = tid >> 5, lane = tid & 31, gi = lane >> 2, q = lane & 3;
  const int dq = 2 * q - 4 * (hl & 1);
  const uint32_t wq = buf + kPrepW + hl * 800 + dq * 40, wp = wq + gi * 2 + 2;
  uint32_t fa[12];
  mbar_wait(bar_phi, 0);
#pragma unroll
  for (int dg = 0; dg < 3; dg++)
#pragma unroll
    for (int fg = 0; fg < 4; fg++) {
      uint32_t lo, hi;
      asm volatile("ld.shared.u16 %0, [%2];\nld.shared.u16 %1, [%2+40];" : "=r"(lo), "=r"(hi) : "r"(fg < 3 ? wp + dg * 320 + fg * 16 : wq + dg * 320) : "memory");
      const uint32_t x = __byte_perm(lo, hi, 0x5410);
      fa[4 * dg + fg] = (dg == 1 || (unsigned)(dq + 8 * dg) < 20u) ? x : 0u;
    }
  mbar_wait(bar, 0);
  uint32_t b[2][3][4];
#pragma unroll
  for (int dg = 2; dg >= 0; dg--) {
    const int c = ((5 * hl) >> 1) + dg;
    const uint32_t a = buf + (c >> 3) * 8192 + lane * 128 + (((c ^ lane) & 7) << 4);
    ldsm4(a, b[0][dg]);
    ldsm4(a + 4096, b[1][dg]);
  }
  asm volatile("bar.sync 3, 256;" ::: "memory");
#pragma unroll
  for (int th = 0; th < 2; th++) {
    uint32_t r[3][4];
#pragma unroll
    for (int tt = 0; tt < 4; tt++) {
      float d0[4] = {0.f, 0.f, 0.f, 0.f}, d1[4] = {0.f, 0.f, 0.f, 0.f};
      mma8(d0, fa[8], fa[9], b[th][2][tt]);
      mma16(d0, fa[0], fa[1], fa[4], fa[5], b[th][0][tt], b[th][1][tt]);
      mma8(d1, fa[10], fa[11], b[th][2][tt]);
      mma16(d1, fa[2], fa[3], fa[6], fa[7], b[th][0][tt], b[th][1][tt]);
      r[0][tt] = pack2(d0[0] - d1[2], d0[1] - d1[3]);
      r[1][tt] = pack2(d0[2] - d1[2], d0[3] - d1[3]);
      r[2][tt] = pack2(d1[0] - d1[2], d1[1] - d1[3]);
    }
    const uint32_t dst = buf + (8 * gi + hl) * 128 + (((4 * th + q) ^ hl) << 4);
#pragma unroll
    for (int fg = 0; fg < 3; fg++) sts128(dst + fg * 8192, r[fg][0], r[fg][1], r[fg][2], r[fg][3]);
  }
  fence_async_smem();
}

__device__ __forceinline__ void prep_wo(uint32_t buf) {
  const int tid = threadIdx.x & 127, w = tid >> 5, lane = tid & 31, gi = lane >> 2, q = lane & 3;
  const int th = w & 1, cb = w >> 1;
  uint32_t v[10][4];
#pragma unroll
  for (int i = 0; i < 10; i++)
    ldsm4t(buf + (i >> 2) * 8192 + th * 4096 + lane * 128 + ((((2 * i + cb) ^ lane) & 7) << 4), v[i]);
  wg_bar(1);
  const int row = 4 * (gi & 2) + 4 * cb + 2 * (gi >> 2) + (gi & 1);
  const uint32_t dst = buf + row * 128 + ((((4 * th + q) ^ row) & 7) << 4);
#pragma unroll
  for (int i = 0; i < 10; i++) sts128(dst + i * 2048, v[i][0], v[i][1], v[i][2], v[i][3]);
  fence_async_smem();
}

__device__ __forceinline__ void b_producer_w(const Params& P, int g) {
  const uint32_t t0 = clock();
#pragma unroll 1
  for (int r = 0; r < 4; r++) {
    const int row = g * 128 + (r >> 1) * 64, k0 = (r & 1) * 320;
#pragma unroll
    for (int s = 0; s < 5; s++) {
      if (r == 0) pace(t0, 600 + s * 600);
      mbar_wait(BAR_EMPTY + 8 * s, (r & 1) ^ 1);
      mbar_expect(BAR_FULL + 8 * s, 16384);
      tma2d(B_RING + s * B_SLOT, &P.bre, k0 + s * 64, row, BAR_FULL + 8 * s);
      tma2d(B_RING + s * B_SLOT + 8192, &P.bim, k0 + s * 64, row, BAR_FULL + 8 * s);
    }
  }
#pragma unroll 1
  for (int ty = 0; ty < 2; ty++) {
#pragma unroll
    for (int st = 0; st < 10; st++) {
      const int s = st % 5, i = (st >> 1) - 1;
      mbar_wait(BAR_EMPTY + 8 * s, st < 5);
      if (st == 6) mbar_arrive1(BAR_W + 8 + 8 * ty);
      mbar_expect(BAR_FULL + 8 * s, 16384);
      tma5d(B_RING + s * B_SLOT, (st & 1) ? &P.cim : &P.cre, (i < 0 ? g : i < g ? i : i + 1) * 128 + ty * 64, 4 * g, 0, BAR_FULL + 8 * s);
    }
  }
}

__device__ __forceinline__ void b_producer_x(const Params& P, int tb, int g) {
  const uint32_t t0 = clock();
  const unsigned done = load_epoch(P);
  const CUtensorMap* xm = tb < 12 ? &P.xb : &P.xbl;
  const int xj = tb < 12 ? 0 : -4, xb = tb < 12 ? tb : 0;
#pragma unroll 1
  for (int r = 0; r < 4; r++) {
#pragma unroll
    for (int s = 0; s < 5; s++) {
      if (r == 0) pace(t0, 600 + s * 600);
      mbar_wait(BAR_EMPTY + 8 * s, (r & 1) ^ 1);
      mbar_expect(BAR_FULL + 8 * s, kBlob);
      tma5d(B_RING + s * B_SLOT + 16384, xm, (r & 1) * 320 + s * 64, xj, xb, BAR_FULL + 8 * s);
    }
  }
#pragma unroll 1
  for (int ty = 0; ty < 2; ty++) {
    const unsigned char* src = P.s->h + (size_t)(tb * 20 + ty * 10) * kBlob;
    uint32_t have = 0;
    mbar_wait(BAR_O + 8 * ty, 0);
#pragma unroll
    for (int st = 0; st < 10; st++) {
      const int s = st % 5, i = (st >> 1) - 1;
      if (st >= 2 && !(st & 1)) {
        if (st == 2) mbar_wait(ty ? BAR_STG1 : BAR_STG, 0);
        const uint32_t need = i < g ? 1 << i : 2 << i;
        if ((have & need) != need) have = uniform(line_wait(P, C_H + (2 * tb + ty) * 32, done + 1, need, 0));
      }
      mbar_wait(BAR_EMPTY + 8 * s, st < 5);
      if (st < 2) {
        mbar_arrive1(BAR_FULL + 8 * s);
      } else {
        mbar_expect(BAR_FULL + 8 * s, kBlob);
        bulk_load(B_RING + s * B_SLOT + 16384, src + (st - (i < g ? 2 : 0)) * kBlob, kBlob, BAR_FULL + 8 * s);
      }
    }
  }
}

__device__ __forceinline__ void b_helper(const Params& P, int bi, int tb, int g, uint32_t c0) {
#pragma unroll 1
  for (int job = bi; job < 120; job += 80) {
    if (job >= 80) {
      while ((uint32_t)clock() - c0 < 7600) __nanosleep(100);
      wo_load(P, bi, B_STG, BAR_P1);
    }
    mbar_wait(job < 80 ? BAR_PREP : BAR_FREE, 0);
    bulk_store(P.s->w + (size_t)tile_pos(job) * kBlob, B_STG, kBlob);
    if (job < 40 && job % 10 < 8) {
#pragma unroll
      for (int i = 0; i < 2; i++) bulk_store(P.s->kv + ((job - job / 10 * 2) * 2 + i) * 2048, B_ZERO, 2048);
    }
    bulk_wait();
    cnt_add(P, tile_counter(job));
  }
  mbar_arrive1(BAR_KVR);
  mbar_wait(BAR_TOK + 8, 0);
  if (bi < 64) {
    prefetch_l2(P.cre_p + bi * 6400, 12800);
    prefetch_l2(P.cim_p + bi * 6400, 12800);
  }
#pragma unroll 1
  for (int ty = 0; ty < 2; ty++) {
    unsigned char* dst = P.s->h + (size_t)(tb * 20 + ty * 10 + 2 * g) * kBlob;
#pragma unroll
    for (int c = 0; c < 5; c++) {
      mbar_wait(c == 4 ? BAR_O + 8 * ty : BAR_X + 8 * (5 * ty + c), 0);
      bulk_store(dst + c * 4096, B_STG + c * 4096, 4096);
      bulk_store(dst + kBlob + c * 4096, B_STG + kBlob + c * 4096, 4096);
    }
    bulk_wait();
    mbar_arrive1(ty ? BAR_STG1 : BAR_STG);
    cnt_add(P, C_H + (2 * tb + ty) * 32 + g);
  }
  mbar_expect(BAR_W, 2 * kBlob);
  mbar_wait(BAR_W + 16, 0);
#pragma unroll
  for (int i = 0; i < 2; i++) tma5d(B_STG + i * kBlob, tb < 12 ? &P.xb : &P.xbl, g * 128 + 64 * i, tb < 12 ? 0 : -4, tb < 12 ? tb : 0, BAR_W);
}

__device__ __forceinline__ void cmul(float ar, float ai, float br, float bi, float& cr, float& ci) {
  const float r = fmaf(ar, br, -ai * bi), i = fmaf(ar, bi, ai * br);
  cr = r; ci = i;
}
__device__ __forceinline__ void cstep(float mr, float mi, float& hr, float& hi, float er, float ei) {
  const float r = fmaf(mr, hr, fmaf(-mi, hi, er)), i = fmaf(mr, hi, fmaf(mi, hr, ei));
  hr = r; hi = i;
}
__device__ __forceinline__ void quad_gather(const float* f, int q, float* o) {
  const bool b0 = q & 1, b1 = q & 2;
  const float mine = b0 ? f[1] : f[0];
  const float r = __shfl_xor_sync(~0u, b0 ? f[0] : f[1], 1);
  const float lo = b0 ? r : mine, hi = b0 ? mine : r;
  const float lo2 = __shfl_xor_sync(~0u, lo, 2), hi2 = __shfl_xor_sync(~0u, hi, 2);
  o[0] = b1 ? lo2 : lo; o[1] = b1 ? hi2 : hi; o[2] = b1 ? lo : lo2; o[3] = b1 ? hi : hi2;
}
__device__ __forceinline__ void quad_scatter(const float* s, int q, float* f) {
  const bool b0 = q & 1, b1 = q & 2;
  const float lo = b1 ? s[2] : s[0], hi = b1 ? s[3] : s[1];
  const float mine = b0 ? hi : lo;
  const float r = __shfl_xor_sync(~0u, b0 ? lo : hi, 1);
  f[0] = b0 ? r : mine; f[1] = b0 ? mine : r;
}

__device__ __forceinline__ void b_consumer(const Params& P, int bi, int tb, int g, int wg) {
  const int tid = threadIdx.x & 127, w = tid >> 5, lane = tid & 31, gi = lane >> 2, q = lane & 3;
  const bool last = tb == 12;

  if (wg) {
    mbar_arrive1(BAR_TOK);
    const int p = 128 * g + tid;
    const float are = ldbf(P.lre + p), aim = ldbf(P.lim + p), ldt = ldbf(P.logdt + p);
    const float dt = __bfloat162float(__float2bfloat16_rn(expf(ldt)));
    const float mag = expf(dt * are);
    float sn, cs;
    sincospif(dt * aim * 0.3183098861837907f, &sn, &cs);
    const float lr = mag * cs, li = mag * sn;
    const float inv = 2.0f * rcp(fmaf(are, are, aim * aim));
    float mr, mi, nr, ni;
    cmul(lr, li, lr, li, nr, ni);
    cmul(nr, ni, nr, ni, nr, ni);
    cmul(nr, ni, nr, ni, nr, ni);
    cmul(nr, ni, nr, ni, mr, mi);
    cmul(mr, mi, mr, mi, mr, mi);
    if (!last) cmul(mr, mi, nr, ni, mr, mi);
    sts128(B_CONST + tid * 16, __float_as_uint(lr), __float_as_uint(li), __float_as_uint(fmaf(lr - 1.0f, are, li * aim) * inv),
           __float_as_uint(fmaf(li, are, (1.0f - lr) * aim) * inv));
    asm volatile("st.shared.v2.f32 [%0], {%1,%2};" ::"r"(B_CONST + 2048 + tid * 8), "f"(mr), "f"(mi) : "memory");
    asm volatile("st.shared.f32 [%0], %1;" ::"r"(B_CONST + 3072 + tid * 4), "f"(ldbf(P.dskip + p)) : "memory");
    asm volatile("st.shared.u32 [%0], %1;" ::"r"(B_CONST + 3584), "r"((load_epoch(P) + 1) & 3) : "memory");
    mbar_arrive1(BAR_V);
    if (bi < 40) {
      mbar_wait(BAR_P1, 0);
      prep_wo(B_STG);
      mbar_arrive1(BAR_FREE);
    }
  }

  float u[80], v[80];
  reg_define<80>(u);
  reg_define<80>(v);
#pragma unroll 1
  for (int it = 0;; it++) {
    const int task = uniform(it);
    mbar_wait(BAR_TOK + 8 * wg, task);
    b_mainloop(u, v, 10 + 10 * task, task ? 0xc03 : 0, BAR_TOK + 8 * (wg ^ 1));
    wg_wait<0>();
    reg_fence<80>(u);
    reg_fence<80>(v);
    if (task) break;
    mbar_arrive1(BAR_EMPTY + 32);

    const int pl = 64 * wg + 16 * w + gi, p = 128 * g + pl + 8 * (q & 1);
    uint32_t tag, k0[4], k1[4];
    float mr, mi;
    mbar_wait(BAR_V, 0);
    asm volatile("ld.shared.u32 %0, [%1];" : "=r"(tag) : "r"(B_CONST + 3584) : "memory");
    lds128(B_CONST + pl * 16, k0);
    lds128(B_CONST + pl * 16 + 128, k1);
    asm volatile("ld.shared.v2.f32 {%0,%1}, [%2];" : "=f"(mr), "=f"(mi) : "r"(B_CONST + 2048 + (pl + 8 * (q & 1)) * 8) : "memory");
    const float Lr[2] = {__uint_as_float(k0[0]), __uint_as_float(k1[0])}, Li[2] = {__uint_as_float(k0[1]), __uint_as_float(k1[1])};
    const float Cr[2] = {__uint_as_float(k0[2]), __uint_as_float(k1[2])}, Ci[2] = {__uint_as_float(k0[3]), __uint_as_float(k1[3])};
    float hr[2] = {0.f, 0.f}, hi[2] = {0.f, 0.f};
#pragma unroll
    for (int t = 0; t < 40; t++)
#pragma unroll
      for (int a = 0; a < 2; a++) {
        const int r = 4 * (t >> 1) + 2 * a + (t & 1);
        cstep(Lr[a], Li[a], hr[a], hi[a], u[r], v[r]);
      }
    float fr[4], fi[4];
    quad_gather(hr, q, fr);
    quad_gather(hi, q, fi);
    float sr = fr[0], si = fi[0];
#pragma unroll
    for (int a = 1; a < 4; a++) cstep(mr, mi, sr, si, fr[a], fi[a]);
    unsigned long long* fin = P.s->fin + tb * 640 + p;
    if (q < 2)
      asm volatile("st.relaxed.gpu.global.v2.b32 [%0], {%1, %2};" ::"l"(fin), "r"((__float_as_uint(sr) & ~3u) | tag), "r"((__float_as_uint(si) & ~3u) | tag) : "memory");
    reg_fence<80>(u);
    reg_fence<80>(v);
#pragma unroll
    for (int a = 0; a < 2; a++) {
      const float kr = Cr[a], ki = Ci[a];
#pragma unroll
      for (int t = 0; t < 40; t++) {
        const int r = 4 * (t >> 1) + 2 * a + (t & 1);
        const float xr = u[r], xi = v[r];
        u[r] = fmaf(kr, xr, -ki * xi);
        v[r] = fmaf(-kr, xi, -ki * xr);
      }
    }
    reg_fence<80>(u);
    reg_fence<80>(v);
    float nr, ni, fr6, fi6;
    cmul(mr, mi, mr, mi, nr, ni);
    cmul(nr, ni, nr, ni, nr, ni);
    if (last) cmul(nr, ni, mr, mi, nr, ni);
    cmul(nr, ni, nr, ni, fr6, fi6);
    cmul(fr6, fi6, nr, ni, fr6, fi6);
    cmul(fr6, fi6, fr6, fi6, fr6, fi6);
    if (q & 2) { fr6 = 1.f; fi6 = 0.f; }
    uint32_t er[6], ei[6];
#pragma unroll
    for (int k = 0; k < 6; k++) er[k] = ei[k] = tag;
    const int back = (q & 2) ? 6 : 12;
    fin -= back * 640;
    uint32_t bad;
    do {
      bad = 0;
#pragma unroll
      for (int k = 0; k < 6; k++)
        asm volatile("{ .reg .pred p; setp.le.s32 p, %3, %4;\n@p ld.relaxed.gpu.global.v2.b32 {%0, %1}, [%2]; }"
                     : "+r"(er[k]), "+r"(ei[k]) : "l"(fin + k * 640), "r"(back - tb), "r"(k) : "memory");
#pragma unroll
      for (int k = 0; k < 6; k++) bad |= (er[k] ^ tag) | (ei[k] ^ tag);
    } while (__any_sync(~0u, bad & 3));
    sr = 0.f; si = 0.f;
#pragma unroll
    for (int k = 0; k < 6; k++) cstep(nr, ni, sr, si, __uint_as_float(er[k] ^ tag), __uint_as_float(ei[k] ^ tag));
    cmul(fr6, fi6, sr, si, sr, si);
    sr += __shfl_xor_sync(~0u, sr, 2);
    si += __shfl_xor_sync(~0u, si, 2);
#pragma unroll
    for (int a = 0; a < 4; a++) {
      const float xr = sr, xi = si;
      cstep(mr, mi, sr, si, fr[a], fi[a]);
      fr[a] = xr; fi[a] = xi;
    }
    quad_scatter(fr, q, hr);
    quad_scatter(fi, q, hi);
#pragma unroll
    for (int a = 0; a < 2; a++) {
      const float xr = hr[a], xi = hi[a];
      hr[a] = fmaf(Cr[a], xr, -Ci[a] * xi);
      hi[a] = fmaf(-Cr[a], xi, -Ci[a] * xr);
    }
    if (last) {
#pragma unroll
      for (int a = 0; a < 2; a++) {
        u[13 + 2 * a] = hr[a]; v[13 + 2 * a] = hi[a];
        hr[a] = 0.f; hi[a] = 0.f;
      }
    }
    const uint32_t ha = B_STG + (lane >> 4) * kBlob + (lane & 7) * 128 + (((2 * w + ((lane >> 3) & 1)) ^ (lane & 7)) << 4);
    mbar_wait(wg ? BAR_STG : BAR_KVR, 0);
    if (wg) mbar_wait(BAR_W + 8, 0);
#pragma unroll
    for (int j = 0; j < 20; j++) {
      uint32_t kr[2], ki[2];
#pragma unroll
      for (int a = 0; a < 2; a++) {
        const int r = 4 * j + 2 * a;
        cstep(Lr[a], -Li[a], hr[a], hi[a], u[r], v[r]);
        const float xr = hr[a], xi = hi[a];
        cstep(Lr[a], -Li[a], hr[a], hi[a], u[r + 1], v[r + 1]);
        kr[a] = pack2(xr, hr[a]);
        ki[a] = pack2(xi, hi[a]);
      }
      stsm4t(ha + j * 1024, kr[0], kr[1], ki[0], ki[1]);
      if ((j & 3) == 3 && j < 19) {
        fence_async_smem();
        mbar_arrive1(BAR_X + 8 * (5 * wg + (j >> 2)));
      }
    }
    fence_async_smem();
    mbar_arrive1(BAR_O + 8 * wg);
    if (wg) {
      mbar_arrive1(BAR_DONE);
      return;
    }
  }

  const int dl = 32 * w + 4 * gi;
  uint32_t dk[4];
  lds128(B_CONST + 3072 + dl * 4, dk);
  const float k0 = __uint_as_float(dk[0]), k1 = __uint_as_float(dk[1]), k2 = __uint_as_float(dk[2]), k3 = __uint_as_float(dk[3]);
  float* o = P.out + (size_t)(last ? 1920 + 32 * q - 8 : 160 * tb + 40 * q) * 1280 + 640 + 128 * g + dl;
  const uint32_t xa = B_STG + (w >> 1) * kBlob + q * 256 + (gi & 1) * 8;
  const uint32_t xc = (4 * (w & 1) + (gi >> 1)) ^ (2 * q);
  mbar_wait(BAR_W, 0);
  mbar_arrive1(BAR_DONE);
#pragma unroll
  for (int t = 0; t < 40; t++) {
    const int r = 4 * (t >> 1) + (t & 1);
    uint32_t x0, x1;
    asm volatile("ld.shared.v2.b32 {%0,%1}, [%2];" : "=r"(x0), "=r"(x1) : "r"(xa + (t >> 1) * 1024 + (t & 1) * 128 + ((xc ^ (t & 1)) << 4)));
    asm volatile("{ .reg .pred p; setp.ne.s32 p, %5, 0;\n@p st.global.v4.f32 [%0], {%1, %2, %3, %4}; }" ::"l"(o + t * 1280),
                 "f"(fmaf(bf_lo(x0), k0, u[r])), "f"(fmaf(bf_hi(x0), k1, u[r + 2])), "f"(fmaf(bf_lo(x1), k2, v[r])), "f"(fmaf(bf_hi(x1), k3, v[r + 2])),
                 "r"((int)(t >= 8 || !last)));
  }
}

__global__ void __launch_bounds__(kThreads, 1) fused_kernel(const __grid_constant__ Params P) {
  extern __shared__ __align__(1024) unsigned char smem[];
  const uint32_t c0 = clock();
  const int b = blockIdx.x;
  const bool isA = b < 128 && (b & 2), isB = !isA && b <= 128;
  const int idx = b < 128 ? (b >> 2) * 2 + (b & 1) : b - 64;
  const int rb = idx & 31, half = idx >> 5;
  const int tb = idx / 5, g = idx % 5;
  const int warp = uniform(threadIdx.x >> 5), wg = warp >> 2;
  if (warp == 8) {
    if (threadIdx.x == 256) {
#pragma unroll
      for (int i = 0; i < 3; i++) mbar_init(BAR_FULL + 8 * i, isB ? 2 : 1);
      mbar_init(isA ? BAR_X : BAR_P, 1);
      mbar_init(isA ? BAR_X + 8 : BAR_KV0, 1);
      mbar_init_fence();
    }
    __syncwarp();
    if (isB) fold_load(P, idx, B_STG, BAR_P, BAR_KV0);
    if (isA) {
#pragma unroll
      for (int n = 0; n < 3; n++) {
        if (n != 1) {
          mbar_expect(BAR_X + 4 * n, 8192);
          tma2d(A_X + n * 4096, &P.xa, n * 32, rb * 64, BAR_X + 4 * n);
        }
        mbar_expect(BAR_FULL + 8 * n, kBlob);
        tma3d(A_RING + n * kBlob, &P.wv, 0, n * 32, 20 + 5 * half, BAR_FULL + 8 * n);
      }
    }
  } else if (threadIdx.x == 288) {
#pragma unroll
    for (uint32_t a = BAR_FULL + 24; a < BAR_FREE; a += 8) {
      if (a == BAR_P || a == BAR_KV0 || a == BAR_X || a == BAR_X + 8) continue;
      mbar_init(a, a < BAR_EMPTY ? (isB ? 2 : 1) : a < BAR_TOK ? (isB ? 4 : 8) : a >= BAR_X ? (isB ? 4 : 1)
                   : (a < BAR_KV0 && a != BAR_STG) ? (isA ? 8 : 4) : 1);
    }
    mbar_init(isA ? BAR_P : BAR_X, isB ? 4 : 1);
    mbar_init(isA ? BAR_KV0 : BAR_X + 8, isB ? 4 : 1);
    mbar_init_fence();
  } else if (threadIdx.x == 320) {
#pragma unroll
    for (uint32_t a = BAR_FREE; a < BAR_END; a += 8)
      mbar_init(a, a < BAR_DONE ? 4 : a == BAR_DONE ? 11 : a == BAR_DUMMY ? 1024 : a == BAR_PREP ? 8 : 1);
    mbar_init_fence();
  }
  __syncthreads();
  if (wg == 2) {
    asm volatile("setmaxnreg.dec.sync.aligned.u32 40;");
    if (warp == 8) {
      if (isA) {
        a_producer(P, rb, half);
      } else if (isB) {
        b_producer_w(P, g);
      } else {
#pragma unroll 1
        for (int n = 0; n < 5; n++) {
          pace(c0, 4000 + n * 500);
          fold_load(P, idx + 3 * n, B_RING + n * 32768, BAR_FULL + 8 * n, BAR_X + 8 * n);
        }
#pragma unroll 1
        for (int n = 0; n < 5; n++) {
          mbar_wait(BAR_EMPTY + 8 * n, 0);
          bulk_store(P.s->w + (size_t)tile_pos(idx + 3 * n) * kBlob, B_RING + n * 32768, kBlob);
        }
        bulk_wait();
        __syncwarp();
        if (threadIdx.x < 261)
          asm volatile("red.release.gpu.global.add.u32 [%0], 1;" ::"l"(P.s->cnt + tile_counter(idx + 3 * (threadIdx.x - 256))) : "memory");
        __syncwarp();
      }
    } else if (warp < 11) {
      if (isA) {
        const unsigned ep = uniform(load_epoch(P) + 1);
        if (warp == 9) a_reducer(P, rb, half, ep);
        else a_poller(P, half, ep);
        a_swap(P, rb, half, warp - 9, ep);
      } else if (isB) {
        if (warp == 9) b_helper(P, idx, tb, g, c0);
        else b_producer_x(P, tb, g);
      }
    } else {
      if ((uint32_t)__cvta_generic_to_shared(smem) != SB) __trap();
      const unsigned done = load_epoch(P);
      const long long t0 = clock64();
      uint32_t ok;
      do {
        asm volatile("{ .reg .pred p; mbarrier.try_wait.parity.shared::cta.b64 p, [%1], 0, 100000; selp.u32 %0, 1, 0, p; }" : "=r"(ok) : "r"(BAR_DONE) : "memory");
        if (clock64() - t0 > 4000000000ll) __trap();
      } while (!ok);
      P.s->ep[b * 32] = done + 1;
    }
    if (warp < 11) mbar_arrive1(BAR_DONE);
  } else {
    asm volatile("setmaxnreg.inc.sync.aligned.u32 232;");
    if (isA) {
      mbar_arrive1(BAR_TOK);
      a_consumer(P, rb, half, wg);
    } else {
      if (threadIdx.x < 128) sts128(B_ZERO + threadIdx.x * 16, 0u, 0u, 0u, 0u);
#pragma unroll 1
      for (int n = 0; n < (isB ? 1 : 5); n++) {
        prep_fold(isB ? B_STG : B_RING + n * 32768, isB ? BAR_P : BAR_FULL + 8 * n, isB ? BAR_KV0 : BAR_X + 8 * n);
        mbar_arrive1(isB ? BAR_PREP : BAR_EMPTY + 8 * n);
      }
      if (isB) b_consumer(P, idx, tb, g, wg);
      else mbar_arrive1(BAR_DONE);
    }
  }
}

typedef CUresult (*EncodeFn)(CUtensorMap*, CUtensorMapDataType, cuuint32_t, void*, const cuuint64_t*, const cuuint64_t*,
                             const cuuint32_t*, const cuuint32_t*, CUtensorMapInterleave, CUtensorMapSwizzle,
                             CUtensorMapL2promotion, CUtensorMapFloatOOBfill);

void encode(EncodeFn fn, CUtensorMap* m, const void* ptr, int rank, const cuuint64_t* dims, const cuuint64_t* strides, const cuuint32_t* box) {
  const cuuint32_t es[5] = {1, 1, 1, 1, 1};
  fn(m, CU_TENSOR_MAP_DATA_TYPE_BFLOAT16, rank, const_cast<void*>(ptr), dims, strides, box, es, CU_TENSOR_MAP_INTERLEAVE_NONE,
     CU_TENSOR_MAP_SWIZZLE_128B, CU_TENSOR_MAP_L2_PROMOTION_L2_128B, CU_TENSOR_MAP_FLOAT_OOB_FILL_NONE);
}

}

extern "C" void kernel_launch(void* const* d_in, const int* in_sizes, int n_in, void* d_out, int out_size) {
  (void)in_sizes; (void)n_in; (void)out_size;
  void* fp = nullptr;
  cudaDriverEntryPointQueryResult qr;
  cudaGetDriverEntryPoint("cuTensorMapEncodeTiled", &fp, cudaEnableDefault, &qr);
  EncodeFn fn = (EncodeFn)fp;
  const __nv_bfloat16* const* in = (const __nv_bfloat16* const*)d_in;
  Params P;
  constexpr cuuint64_t R = kD * 2;
  {
    const cuuint64_t d[2] = {kD, kSeq}, s[1] = {R};
    const cuuint32_t b[2] = {64, 64};
    encode(fn, &P.xa, in[0], 2, d, s, b);
  }
  {
    const cuuint64_t d[3] = {64, kD, 30}, s[2] = {3 * R, 128};
    const cuuint32_t b[3] = {64, 32, 5};
    encode(fn, &P.wv, in[1], 3, d, s, b);
  }
  {
    const cuuint64_t d[5] = {kD, 2, 4, 20, 12}, s[4] = {R, 40 * R, 2 * R, 160 * R};
    const cuuint32_t b[5] = {64, 2, 4, 20, 1};
    encode(fn, &P.xb, in[4], 5, d, s, b);
    const cuuint64_t dl[5] = {kD, 2, 4, 16, 1}, sl[4] = {R, 32 * R, 2 * R, 160 * R};
    encode(fn, &P.xbl, in[4] + 1920 * kD, 5, dl, sl, b);
  }
  {
    const cuuint64_t d[2] = {kD, kD}, s[1] = {R};
    const cuuint32_t b[2] = {64, 64};
    encode(fn, &P.bre, in[7], 2, d, s, b);
    encode(fn, &P.bim, in[8], 2, d, s, b);
  }
  {
    const cuuint64_t d[5] = {kD, 8, 2, 20, 2}, s[4] = {4 * R, R, 32 * R, 2 * R};
    const cuuint32_t b[5] = {64, 8, 2, 4, 2};
    encode(fn, &P.cre, in[9], 5, d, s, b);
    encode(fn, &P.cim, in[10], 5, d, s, b);
  }
  {
    const cuuint64_t d[5] = {3 * kD, 2, 4, 4, 20}, s[4] = {3 * R, 24 * R, 6 * R, 96 * R};
    const cuuint32_t b[5] = {64, 2, 4, 4, 1}, b2[5] = {64, 2, 4, 4, 2};
    encode(fn, &P.wp, in[1], 5, d, s, b2);
    const cuuint64_t d2[5] = {kD, 2, 4, 4, 20}, s2[4] = {R, 8 * R, 2 * R, 32 * R};
    encode(fn, &P.wop, in[3], 5, d2, s2, b);
  }
  P.wphi = in[2]; P.cre_p = in[9]; P.cim_p = in[10];
  P.lre = in[5]; P.lim = in[6]; P.logdt = in[11]; P.dskip = in[12];
  P.out = (float*)d_out;
  P.one = 1;
  cudaGetSymbolAddress((void**)&P.s, g_scratch);
  cudaFuncSetAttribute(fused_kernel, cudaFuncAttributeMaxDynamicSharedMemorySize, kSmem);
  fused_kernel<<<kGrid, kThreads, kSmem>>>(P);
}
```
